```python
import torch

def _softmax(x, axis=-1):
    return torch.softmax(x, dim=axis)
def _gelu(x):
    return torch.nn.functional.gelu(x, approximate="tanh")
def _silu(x):
    return torch.nn.functional.silu(x)
def _sigmoid(x):
    return torch.sigmoid(x)
def _layernorm(x, axis=-1, eps=1e-5):
    m = x.mean(dim=axis, keepdim=True)
    v = x.var(dim=axis, keepdim=True, unbiased=False)
    return (x - m) / torch.sqrt(v + eps)
def _scatter_add(tgt, idx, src, axis=0):
    return tgt.clone().index_add_(axis, idx, src)
def _segment_sum(src, seg, n):
    out = torch.zeros((n,) + src.shape[1:], dtype=src.dtype)
    return out.index_add_(0, seg, src)
def _pad(x, pw):
    flat = tuple(v for pair in reversed(pw) for v in pair)
    return torch.nn.functional.pad(x, flat)

kernel_name = 'standalone__mha_softmax__near_ridge'

def setup_inputs():

    _w = (lambda a: (lambda t: t.to(torch.bfloat16) if t.is_floating_point() else t)(torch.as_tensor(a)))
    B, H, Sq, Sk, D = 32, 16, 384, 384, 256
    return {
        "q": _w((lambda *s: torch.randn(*s, dtype=torch.bfloat16) * 0.8)(B, H, Sq, D)),
        "k": _w((lambda *s: torch.randn(*s, dtype=torch.bfloat16) * 0.8)(B, H, Sk, D)),
        "v": _w((lambda *s: torch.randn(*s, dtype=torch.bfloat16) * 0.05)(B, H, Sk, D)),
    }

def reference(q, k, v):
    scale = q.shape[-1] ** -0.5
    scores = torch.einsum("bhqd,bhkd->bhqk", q, k) * scale
    p = _softmax(scores, axis=-1)
    return torch.einsum("bhqk,bhkd->bhqd", p, v)
```

```cpp
#include <cuda_runtime.h>
#include <cuda_bf16.h>
#include <cuda.h>
#include <stdint.h>

namespace {

constexpr int kSeq = 384;
constexpr int kHeads = 512;
constexpr int kClusters = 64;
constexpr int kHeadsPerCluster = kHeads / kClusters;
constexpr int kSlots = 14;
constexpr int kSlotBytes = 16384;
constexpr int kUnits = 30;
constexpr int kThreads = 512;
constexpr int kSmemBytes = kSlots * kSlotBytes + 1024   + 1024  ;
constexpr uint32_t kEmptyCount = 24;

constexpr int kIdx(int u) { return u < 4 ? 2 + u : 6 + u; }
constexpr int qIdx(int w, int h) { return w == 0 ? h : 4 + 2 * w + h; }
struct Sched {
  uint32_t cons[kHeadsPerCluster][12];
  uint8_t prod[kHeadsPerCluster][32];
};
constexpr Sched makeSched() {
  Sched s{};
  int rel[kUnits] = {};
  int n = 0;
  for (int g = 0; g < 3; g++)
    for (int w = 0; w < 3; w++)
      for (int a = 0; a < 4; a++) {
        if (w == 2) rel[n++] = kIdx(g * 4 + a);
        if (g == 2 && (a & 1)) rel[n++] = qIdx(w, a / 2);
      }
  for (int x = 0; x < 12; x++) rel[n++] = 18 + x;
  int slot[kHeadsPerCluster * kUnits] = {};
  int uses[kSlots] = {};
  for (int i = 0; i < kHeadsPerCluster * kUnits; i++) {
    int sl = i;
    if (i >= kSlots) {
      int k = i - kSlots;
      sl = slot[(k / kUnits) * kUnits + rel[k % kUnits]];
    }
    slot[i] = sl;
    s.prod[i / kUnits][i % kUnits] = (uint8_t)(sl | ((uses[sl] & 1) << 4));
    uses[sl]++;
  }
  for (int h = 0; h < kHeadsPerCluster; h++) {
    for (int g = 0; g < 3; g++)
      for (int a = 0; a < 4; a++) s.cons[h][g] |= (uint32_t)s.prod[h][kIdx(g * 4 + a)] << (8 * a);
    for (int c = 0; c < 4; c++)
      for (int a = 0; a < 3; a++) s.cons[h][3 + c] |= (uint32_t)s.prod[h][18 + c * 3 + a] << (8 * a);
    for (int w = 0; w < 3; w++)
      for (int a = 0; a < 2; a++) s.cons[h][8 + w] |= (uint32_t)s.prod[h][qIdx(w, a)] << (8 * a);
  }
  return s;
}
__constant__ Sched c_sched = makeSched();

__device__ __forceinline__ uint32_t smem_u32(const void* p) { return (uint32_t)__cvta_generic_to_shared(p); }
__device__ __forceinline__ void mbar_init(uint32_t bar, uint32_t cnt) {
  asm volatile("mbarrier.init.shared::cta.b64 [%0], %1;" ::"r"(bar), "r"(cnt) : "memory");
}
__device__ __forceinline__ void mbar_expect_tx(uint32_t bar, uint32_t bytes) {
  asm volatile("mbarrier.arrive.expect_tx.shared::cta.b64 _, [%0], %1;" ::"r"(bar), "r"(bytes) : "memory");
}
__device__ __forceinline__ void mbar_wait(uint32_t bar, uint32_t parity) {
  asm volatile(
      "{\n"
      ".reg .pred p;\n"
      ".reg .u32 n;\n"
      "mov.u32 n, 0;\n"
      "LAB_WAIT:\n"
      "mbarrier.try_wait.parity.shared::cta.b64 p, [%0], %1;\n"
      "@p bra LAB_DONE;\n"
      "add.u32 n, n, 1;\n"
      "setp.lt.u32 p, n, 0x400000;\n"
      "@p bra LAB_WAIT;\n"
      "trap;\n"
      "LAB_DONE:\n"
      "}\n" ::"r"(bar),
      "r"(parity)
      : "memory");
}
__device__ __forceinline__ uint32_t map_to_cta(uint32_t addr, uint32_t cta) {
  uint32_t r;
  asm("mapa.shared::cluster.u32 %0, %1, %2;" : "=r"(r) : "r"(addr), "r"(cta));
  return r;
}
__device__ __forceinline__ void release_slot(uint32_t bar, uint32_t lane, uint32_t count) {
  asm volatile(
      "{\n"
      ".reg .pred p;\n"
      "setp.lt.u32 p, %1, 2;\n"
      "@p mbarrier.arrive.shared::cluster.b64 _, [%0], %2;\n"
      "}\n" ::"r"(bar),
      "r"(lane), "r"(count)
      : "memory");
}
__device__ __forceinline__ void tma_load(uint32_t dst, const CUtensorMap* m, uint32_t bar, int row, int cb) {
  asm volatile(
      "cp.async.bulk.tensor.3d.shared::cluster.global.mbarrier::complete_tx::bytes [%0], [%1, {%3, %4, %5}], [%2];" ::"r"(dst),
      "l"(m), "r"(bar), "r"(0), "r"(row), "r"(cb)
      : "memory");
}
__device__ __forceinline__ void tma_load_mc(uint32_t dst, const CUtensorMap* m, uint32_t bar, int row, int cb) {
  asm volatile(
      "cp.async.bulk.tensor.3d.shared::cluster.global.mbarrier::complete_tx::bytes.multicast::cluster [%0], [%1, {%3, %4, "
      "%5}], [%2], %6;" ::"r"(dst),
      "l"(m), "r"(bar), "r"(0), "r"(row), "r"(cb), "h"((uint16_t)3)
      : "memory");
}
__device__ __forceinline__ void cluster_arrive() { asm volatile("barrier.cluster.arrive.release.aligned;" ::: "memory"); }
__device__ __forceinline__ void cluster_wait() { asm volatile("barrier.cluster.wait.acquire.aligned;" ::: "memory"); }
__device__ __forceinline__ void turn_wait(int id) { asm volatile("bar.sync %0, 256;" ::"r"(id) : "memory"); }
__device__ __forceinline__ void turn_pass(int id) { asm volatile("bar.arrive %0, 256;" ::"r"(id) : "memory"); }
__device__ __forceinline__ void wg_fence() { asm volatile("wgmma.fence.sync.aligned;" ::: "memory"); }
__device__ __forceinline__ void wg_commit() { asm volatile("wgmma.commit_group.sync.aligned;" ::: "memory"); }
template <int N>
__device__ __forceinline__ void wg_wait() {
  asm volatile("wgmma.wait_group.sync.aligned %0;" ::"n"(N) : "memory");
}
__device__ __forceinline__ float ex2(float x) {
  float y;
  asm("ex2.approx.ftz.f32 %0, %1;" : "=f"(y) : "f"(x));
  return y;
}
__device__ __forceinline__ uint32_t pack_bf16(float lo, float hi) {
  uint32_t r;
  asm("cvt.rn.bf16x2.f32 %0, %1, %2;" : "=r"(r) : "f"(hi), "f"(lo));
  return r;
}
__device__ __forceinline__ void scale_bf16x2(uint32_t& x, uint32_t fh, uint32_t fl) {
  asm("{\n.reg .b32 t;\nmul.rn.bf16x2 t, %0, %2;\nfma.rn.bf16x2 %0, %0, %1, t;\n}\n" : "+r"(x) : "r"(fh), "r"(fl));
}
__device__ __forceinline__ float rcp(float x) {
  float y;
  asm("rcp.approx.ftz.f32 %0, %1;" : "=f"(y) : "f"(x));
  return y;
}

constexpr uint32_t kDescHi = 64u | (1u << 30);
__device__ __forceinline__ uint32_t desc_lo(uint32_t addr) { return ((addr & 0x3FFFF) >> 4) | (1u << 16); }

#define ACC8(a, o) \
  "+f"(a[o]), "+f"(a[o + 1]), "+f"(a[o + 2]), "+f"(a[o + 3]), "+f"(a[o + 4]), "+f"(a[o + 5]), "+f"(a[o + 6]), "+f"(a[o + 7])
#define IN8(a, o) \
  "r"(a[o]), "r"(a[o + 1]), "r"(a[o + 2]), "r"(a[o + 3]), "r"(a[o + 4]), "r"(a[o + 5]), "r"(a[o + 6]), "r"(a[o + 7])
#define REGS32 "{%0,%1,%2,%3,%4,%5,%6,%7,%8,%9,%10,%11,%12,%13,%14,%15,%16,%17,%18,%19,%20,%21,%22,%23,%24,%25,%26,%27,%28,%29,%30,%31}"
#define REGS64 "{%0,%1,%2,%3,%4,%5,%6,%7,%8,%9,%10,%11,%12,%13,%14,%15,%16,%17,%18,%19,%20,%21,%22,%23,%24,%25,%26,%27,%28,%29,%30,%31,%32,%33,%34,%35,%36,%37,%38,%39,%40,%41,%42,%43,%44,%45,%46,%47,%48,%49,%50,%51,%52,%53,%54,%55,%56,%57,%58,%59,%60,%61,%62,%63}"

__device__ __forceinline__ void mma_qk(float (&d)[64], uint32_t qa, uint32_t kb, int accumulate) {
  asm volatile(
      "{\n.reg .pred p;\n.reg .b32 a, b;\n.reg .b64 da, db;\n"
      "setp.ne.b32 p, %66, 0;\n"
      "wgmma.fence.sync.aligned;\n"
      "mov.b64 da, {%64, %67};\nmov.b64 db, {%65, %67};\n"
      "wgmma.mma_async.sync.aligned.m64n128k16.f32.bf16.bf16 " REGS64 ", da, db, p, 1, 1, 0, 0;\n"
      "add.u32 a, %64, 2;\nadd.u32 b, %65, 2;\nmov.b64 da, {a, %67};\nmov.b64 db, {b, %67};\n"
      "wgmma.mma_async.sync.aligned.m64n128k16.f32.bf16.bf16 " REGS64 ", da, db, 1, 1, 1, 0, 0;\n"
      "add.u32 a, %64, 4;\nadd.u32 b, %65, 4;\nmov.b64 da, {a, %67};\nmov.b64 db, {b, %67};\n"
      "wgmma.mma_async.sync.aligned.m64n128k16.f32.bf16.bf16 " REGS64 ", da, db, 1, 1, 1, 0, 0;\n"
      "add.u32 a, %64, 6;\nadd.u32 b, %65, 6;\nmov.b64 da, {a, %67};\nmov.b64 db, {b, %67};\n"
      "wgmma.mma_async.sync.aligned.m64n128k16.f32.bf16.bf16 " REGS64 ", da, db, 1, 1, 1, 0, 0;\n"
      "wgmma.commit_group.sync.aligned;\n}\n"
      : ACC8(d, 0), ACC8(d, 8), ACC8(d, 16), ACC8(d, 24), ACC8(d, 32), ACC8(d, 40), ACC8(d, 48), ACC8(d, 56)
      : "r"(qa), "r"(kb), "r"(accumulate), "n"(kDescHi)
      : "memory");
}
__device__ __forceinline__ void mma_pv(float (&d)[32], const uint32_t* a, uint32_t vb, int accumulate) {
  asm volatile(
      "{\n.reg .pred p;\n.reg .b32 b;\n.reg .b64 db;\n"
      "setp.ne.b32 p, %65, 0;\n"
      "wgmma.fence.sync.aligned;\n"
      "mov.b64 db, {%64, %66};\n"
      "wgmma.mma_async.sync.aligned.m64n64k16.f32.bf16.bf16 " REGS32 ", {%32,%33,%34,%35}, db, p, 1, 1, 1;\n"
      "add.u32 b, %64, 128;\nmov.b64 db, {b, %66};\n"
      "wgmma.mma_async.sync.aligned.m64n64k16.f32.bf16.bf16 " REGS32 ", {%36,%37,%38,%39}, db, 1, 1, 1, 1;\n"
      "add.u32 b, %64, 256;\nmov.b64 db, {b, %66};\n"
      "wgmma.mma_async.sync.aligned.m64n64k16.f32.bf16.bf16 " REGS32 ", {%40,%41,%42,%43}, db, 1, 1, 1, 1;\n"
      "add.u32 b, %64, 384;\nmov.b64 db, {b, %66};\n"
      "wgmma.mma_async.sync.aligned.m64n64k16.f32.bf16.bf16 " REGS32 ", {%44,%45,%46,%47}, db, 1, 1, 1, 1;\n"
      "add.u32 b, %64, 512;\nmov.b64 db, {b, %66};\n"
      "wgmma.mma_async.sync.aligned.m64n64k16.f32.bf16.bf16 " REGS32 ", {%48,%49,%50,%51}, db, 1, 1, 1, 1;\n"
      "add.u32 b, %64, 640;\nmov.b64 db, {b, %66};\n"
      "wgmma.mma_async.sync.aligned.m64n64k16.f32.bf16.bf16 " REGS32 ", {%52,%53,%54,%55}, db, 1, 1, 1, 1;\n"
      "add.u32 b, %64, 768;\nmov.b64 db, {b, %66};\n"
      "wgmma.mma_async.sync.aligned.m64n64k16.f32.bf16.bf16 " REGS32 ", {%56,%57,%58,%59}, db, 1, 1, 1, 1;\n"
      "add.u32 b, %64, 896;\nmov.b64 db, {b, %66};\n"
      "wgmma.mma_async.sync.aligned.m64n64k16.f32.bf16.bf16 " REGS32 ", {%60,%61,%62,%63}, db, 1, 1, 1, 1;\n"
      "wgmma.commit_group.sync.aligned;\n}\n"
      : ACC8(d, 0), ACC8(d, 8), ACC8(d, 16), ACC8(d, 24)
      : IN8(a, 0), IN8(a, 8), IN8(a, 16), IN8(a, 24), "r"(vb), "r"(accumulate), "n"(kDescHi)
      : "memory");
}
template <int N>
__device__ __forceinline__ void keep_regs(float (&d)[N]) {
#pragma unroll
  for (int i = 0; i < N; i++) asm volatile("" : "+f"(d[i])::"memory");
}

__device__ __forceinline__ uint4 quad_transpose(uint32_t a0, uint32_t a1, uint32_t a2, uint32_t a3, bool b0, bool b1) {
  uint32_t s0 = b0 ? a0 : a1, s1 = b0 ? a2 : a3;
  uint32_t r0 = __shfl_xor_sync(0xffffffffu, s0, 1), r1 = __shfl_xor_sync(0xffffffffu, s1, 1);
  uint32_t c0 = b0 ? r0 : a0, c1 = b0 ? a1 : r0, c2 = b0 ? r1 : a2, c3 = b0 ? a3 : r1;
  uint32_t t0 = b1 ? c0 : c2, t1 = b1 ? c1 : c3;
  uint32_t u0 = __shfl_xor_sync(0xffffffffu, t0, 2), u1 = __shfl_xor_sync(0xffffffffu, t1, 2);
  uint4 r;
  r.x = b1 ? u0 : c0;
  r.y = b1 ? u1 : c1;
  r.z = b1 ? c2 : u0;
  r.w = b1 ? c3 : u1;
  return r;
}

constexpr float kScaleLog2 = 0.0625f * 1.4426950408889634f;

__device__ __forceinline__ void softmax_chunk(float (&s)[64], float (&m)[2], float (&l)[2], bool first) {
  float mx0 = fmaxf(s[0], s[1]), mx1 = fmaxf(s[2], s[3]);
#pragma unroll
  for (int i = 1; i < 16; i++) {
    mx0 = fmaxf(mx0, fmaxf(s[4 * i], s[4 * i + 1]));
    mx1 = fmaxf(mx1, fmaxf(s[4 * i + 2], s[4 * i + 3]));
  }
  mx0 = fmaxf(mx0, __shfl_xor_sync(0xffffffffu, mx0, 1));
  mx1 = fmaxf(mx1, __shfl_xor_sync(0xffffffffu, mx1, 1));
  mx0 = fmaxf(mx0, __shfl_xor_sync(0xffffffffu, mx0, 2));
  mx1 = fmaxf(mx1, __shfl_xor_sync(0xffffffffu, mx1, 2));
  mx0 *= kScaleLog2;
  mx1 *= kScaleLog2;
  if (!first) {
    mx0 = fmaxf(mx0, m[0]);
    mx1 = fmaxf(mx1, m[1]);
  }
  float a0 = 0.f, a1 = 0.f, b0 = 0.f, b1 = 0.f;
#pragma unroll
  for (int i = 0; i < 16; i++) {
    s[4 * i] = ex2(fmaf(s[4 * i], kScaleLog2, -mx0));
    s[4 * i + 1] = ex2(fmaf(s[4 * i + 1], kScaleLog2, -mx0));
    s[4 * i + 2] = ex2(fmaf(s[4 * i + 2], kScaleLog2, -mx1));
    s[4 * i + 3] = ex2(fmaf(s[4 * i + 3], kScaleLog2, -mx1));
    a0 += s[4 * i];
    b0 += s[4 * i + 1];
    a1 += s[4 * i + 2];
    b1 += s[4 * i + 3];
  }
  if (first) {
    l[0] = a0 + b0;
    l[1] = a1 + b1;
  } else {
    l[0] = fmaf(l[0], ex2(m[0] - mx0), a0 + b0);
    l[1] = fmaf(l[1], ex2(m[1] - mx1), a1 + b1);
  }
  m[0] = mx0;
  m[1] = mx1;
}

__global__ void __cluster_dims__(2, 1, 1) __launch_bounds__(kThreads, 1)
    mha_kernel(const __grid_constant__ CUtensorMap mapQ, const __grid_constant__ CUtensorMap mapK,
               const __grid_constant__ CUtensorMap mapV, __nv_bfloat16* __restrict__ out) {
  extern __shared__ unsigned char smem_raw[];
  const uint32_t base = (smem_u32(smem_raw) + 1023u) & ~1023u;
  const uint32_t bar_full = base + kSlots * kSlotBytes;
  const uint32_t bar_empty = bar_full + 128;
  const int wg = __shfl_sync(0xffffffffu, (int)(threadIdx.x >> 7), 0);
  const int rank = blockIdx.x & 1;
  const int cid = blockIdx.x >> 1;

  if (threadIdx.x == 0) {
#pragma unroll
    for (int i = 0; i < kSlots; i++) {
      mbar_init(bar_full + 8 * i, 1);
      mbar_init(bar_empty + 8 * i, kEmptyCount);
    }
    asm volatile("fence.mbarrier_init.release.cluster;" ::: "memory");
  }
  __syncthreads();
  cluster_arrive();
  cluster_wait();

  if (wg == 3) {
    asm volatile("setmaxnreg.dec.sync.aligned.u32 32;");
    if (threadIdx.x == 384) {
#pragma unroll 1
      for (int h = 0; h < kHeadsPerCluster; h++) {
        const int row0 = (cid + h * kClusters) * kSeq;
#pragma unroll 1
        for (int u = 0; u < kUnits; u++) {
          const uint32_t e = c_sched.prod[h][u];
          const uint32_t sl = e & 15u;
          const uint32_t dst = base + sl * kSlotBytes, fb = bar_full + 8 * sl;
          mbar_wait(bar_empty + 8 * sl, (e >> 4) ^ 1u);
          mbar_expect_tx(fb, kSlotBytes);
          if (u < 2 || (u >= 6 && u < 10)) {
            const int w = u < 2 ? 0 : (u - 4) >> 1;
            tma_load(dst, &mapQ, fb, row0 + rank * 192 + w * 64, (u & 1) * 2);
          } else if (u < 18) {
            const int ku = u < 6 ? u - 2 : u - 6;
            tma_load_mc(dst + rank * 8192, &mapK, fb, row0 + (ku >> 2) * 128 + rank * 64, ku & 3);
          } else {
            const int vu = u - 18, c = vu / 3;
            tma_load_mc(dst + rank * 8192, &mapV, fb, row0 + (vu - 3 * c) * 128 + rank * 64, c);
          }
        }
      }
    }
    __syncwarp();
  } else {
    asm volatile("setmaxnreg.inc.sync.aligned.u32 160;");
    const uint32_t lane = threadIdx.x & 31;
    const uint32_t dbase = desc_lo(base);
    const uint32_t rel_bar = map_to_cta(bar_empty, lane & 1);
    const int my_turn = 1 + wg, next_turn = 1 + (wg == 2 ? 0 : wg + 1);
    if (wg == 2) turn_pass(1);
    const bool b0 = lane & 1, b1 = lane & 2;
    const uint32_t out_off =
        (uint32_t)(rank * 192 + wg * 64 + ((threadIdx.x >> 5) & 3) * 16 + (lane >> 2)) * 512u + (lane & 3) * 16u;

#pragma unroll 1
    for (int h = 0; h < kHeadsPerCluster; h++) {
      uint32_t P[96];
      float m[2], l[2], m0[2], m1[2];
      const uint32_t qw = c_sched.cons[h][8 + wg];
      const uint32_t q0 = qw & 15u, q1 = (qw >> 8) & 15u;

#pragma unroll
      for (int j = 0; j < 3; j++) {
        float s[64];
        const uint32_t kw = c_sched.cons[h][j];
        turn_wait(my_turn);
#pragma unroll
        for (int cb = 0; cb < 4; cb++) {
          const uint32_t e = kw >> (8 * cb), sl = e & 15u;
          if (j == 0 && cb == 0) mbar_wait(bar_full + 8 * q0, (qw >> 4) & 1u);
          if (j == 0 && cb == 2) mbar_wait(bar_full + 8 * q1, (qw >> 12) & 1u);
          mbar_wait(bar_full + 8 * sl, (e >> 4) & 1u);
          mma_qk(s, dbase + (cb < 2 ? q0 : q1) * 1024 + (cb & 1) * 512, dbase + sl * 1024, cb != 0);
        }
        turn_pass(next_turn);
        wg_wait<3>();
        release_slot(rel_bar + 8 * (kw & 15u), lane, 1);
        wg_wait<2>();
        release_slot(rel_bar + 8 * ((kw >> 8) & 15u), lane, 1);
        if (j == 2) release_slot(rel_bar + 8 * q0, lane, 3);
        wg_wait<1>();
        release_slot(rel_bar + 8 * ((kw >> 16) & 15u), lane, 1);
        wg_wait<0>();
        keep_regs(s);
        release_slot(rel_bar + 8 * ((kw >> 24) & 15u), lane, 1);
        if (j == 2) release_slot(rel_bar + 8 * q1, lane, 3);

        softmax_chunk(s, m, l, j == 0);
        if (j == 0) { m0[0] = m[0]; m0[1] = m[1]; }
        if (j == 1) { m1[0] = m[0]; m1[1] = m[1]; }
#pragma unroll
        for (int i = 0; i < 32; i++) P[32 * j + i] = pack_bf16(s[2 * i], s[2 * i + 1]);
      }
      l[0] += __shfl_xor_sync(0xffffffffu, l[0], 1);
      l[1] += __shfl_xor_sync(0xffffffffu, l[1], 1);
      l[0] += __shfl_xor_sync(0xffffffffu, l[0], 2);
      l[1] += __shfl_xor_sync(0xffffffffu, l[1], 2);
      {
        const float i0 = rcp(l[0]), i1 = rcp(l[1]);
#pragma unroll
        for (int j = 0; j < 3; j++) {
          const float f0 = j == 2 ? i0 : ex2((j ? m1[0] : m0[0]) - m[0]) * i0;
          const float f1 = j == 2 ? i1 : ex2((j ? m1[1] : m0[1]) - m[1]) * i1;
          const uint32_t h0 = pack_bf16(f0, f0), h1 = pack_bf16(f1, f1);
          const float r0 = f0 - __uint_as_float(h0 << 16), r1 = f1 - __uint_as_float(h1 << 16);
          const uint32_t l0 = pack_bf16(r0, r0), l1 = pack_bf16(r1, r1);
#pragma unroll
          for (int i = 0; i < 16; i++) {
            scale_bf16x2(P[32 * j + 2 * i], h0, l0);
            scale_bf16x2(P[32 * j + 2 * i + 1], h1, l1);
          }
        }
      }

      char* optr = reinterpret_cast<char*>(out) + (size_t)(cid + h * kClusters) * (kSeq * 512) + out_off;
#pragma unroll 1
      for (int c = 0; c < 4; c++) {
        float o[32];
        const uint32_t vw = c_sched.cons[h][3 + c];
        turn_wait(my_turn);
#pragma unroll
        for (int j = 0; j < 3; j++) {
          const uint32_t e = vw >> (8 * j), sl = e & 15u;
          mbar_wait(bar_full + 8 * sl, (e >> 4) & 1u);
          mma_pv(o, P + 32 * j, dbase + sl * 1024, j != 0);
        }
        if (!(wg == 2 && c == 3 && h == kHeadsPerCluster - 1)) turn_pass(next_turn);
        wg_wait<2>();
        release_slot(rel_bar + 8 * (vw & 15u), lane, 1);
        wg_wait<1>();
        release_slot(rel_bar + 8 * ((vw >> 8) & 15u), lane, 1);
        wg_wait<0>();
        keep_regs(o);
        release_slot(rel_bar + 8 * ((vw >> 16) & 15u), lane, 1);
#pragma unroll
        for (int q = 0; q < 2; q++) {
#pragma unroll
          for (int r = 0; r < 2; r++) {
            const int b = 16 * q + 2 * r;
            const uint4 v = quad_transpose(pack_bf16(o[b], o[b + 1]), pack_bf16(o[b + 4], o[b + 5]),
                                           pack_bf16(o[b + 8], o[b + 9]), pack_bf16(o[b + 12], o[b + 13]), b0, b1);
            *reinterpret_cast<uint4*>(optr + r * 4096 + q * 64) = v;
          }
        }
        optr += 128;
      }
    }
  }
  cluster_arrive();
  cluster_wait();
}

typedef CUresult (*EncodeTiledFn)(CUtensorMap*, CUtensorMapDataType, cuuint32_t, void*, const cuuint64_t*,
                                  const cuuint64_t*, const cuuint32_t*, const cuuint32_t*, CUtensorMapInterleave,
                                  CUtensorMapSwizzle, CUtensorMapL2promotion, CUtensorMapFloatOOBfill);

CUtensorMap make_map(EncodeTiledFn enc, const void* ptr, uint32_t boxBlocks) {
  CUtensorMap m;
  cuuint64_t dims[3] = {64, (cuuint64_t)kHeads * kSeq, 4};
  cuuint64_t strides[2] = {512, 128};
  cuuint32_t box[3] = {64, 64, boxBlocks};
  cuuint32_t es[3] = {1, 1, 1};
  enc(&m, CU_TENSOR_MAP_DATA_TYPE_BFLOAT16, 3, const_cast<void*>(ptr), dims, strides, box, es,
      CU_TENSOR_MAP_INTERLEAVE_NONE, CU_TENSOR_MAP_SWIZZLE_128B, CU_TENSOR_MAP_L2_PROMOTION_L2_128B,
      CU_TENSOR_MAP_FLOAT_OOB_FILL_NONE);
  return m;
}

}

extern "C" void kernel_launch(void* const* d_in, const int* in_sizes, int n_in, void* d_out, int out_size) {
  static EncodeTiledFn enc = nullptr;
  if (!enc) {
    void* fn = nullptr;
    cudaDriverEntryPointQueryResult qr;
    cudaGetDriverEntryPoint("cuTensorMapEncodeTiled", &fn, cudaEnableDefault, &qr);
    enc = (EncodeTiledFn)fn;
    cudaFuncSetAttribute(mha_kernel, cudaFuncAttributeMaxDynamicSharedMemorySize, kSmemBytes);
  }
  const CUtensorMap mq = make_map(enc, d_in[0], 2);
  const CUtensorMap mk = make_map(enc, d_in[1], 1);
  const CUtensorMap mv = make_map(enc, d_in[2], 1);
  mha_kernel<<<2 * kClusters, kThreads, kSmemBytes, cudaStreamPerThread>>>(mq, mk, mv, (__nv_bfloat16*)d_out);
}
```

```cpp
#include <cuda_runtime.h>
#include <cuda_bf16.h>
#include <cuda.h>
#include <stdint.h>
#include <type_traits>

namespace {

constexpr int kSeq = 384;
constexpr int kHeads = 512;
constexpr int kClusters = 64;
constexpr int kHeadsPerCluster = kHeads / kClusters;
constexpr int kSlots = 14;
constexpr int kSlotBytes = 16384;
constexpr int kUnits = 30;
constexpr int kThreads = 512;
constexpr int kSmemBytes = kSlots * kSlotBytes + 1024   + 1024  ;
constexpr uint32_t kEmptyCount = 24;

#define DEFER 3
#define PACE 0
#define PFN 0
#define EFU 197
#define DELTA 235
#define DSKIP 8
#define POFF 72
#define PEND 70
constexpr int kIdx(int u) { return u < 4 ? 2 + u : 6 + u; }
constexpr int qIdx(int w, int h) { return w == 0 ? h : 4 + 2 * w + h; }
struct Sched {
  uint32_t cons[kHeadsPerCluster][12];
  uint32_t prod[kHeadsPerCluster * kUnits];
};
constexpr int kLastVs[5][12] = {{4, 5, 6, 7, 8, 9, 10, 11, 12, 13, 14, 15},
                                {8, 9, 10, 12, 13, 15, 18, 19, 20, 21, 22, 23},
                                {4, 5, 6, 12, 13, 15, 18, 19, 20, 21, 22, 23},
                                {4, 5, 6, 8, 9, 10, 12, 13, 15, 18, 19, 20},
                                {8, 9, 10, 11, 12, 13, 14, 15, 16, 18, 19, 20}};
constexpr const int* kLastV = kLastVs[DEFER];
constexpr Sched makeSched() {
  Sched s{};
  int rel[kUnits] = {};
  int n = 0;
  for (int g = 0; g < 3; g++)
    for (int w = 0; w < 3; w++)
      for (int a = 0; a < 4; a++) {
        if (w == 2) rel[n++] = kIdx(g * 4 + a);
        if (g == 2 && (a & 1)) rel[n++] = qIdx(w, a / 2);
      }
  for (int x = 0; x < 12; x++) rel[n++] = 18 + x;
  int slot[kHeadsPerCluster * kUnits] = {};
  uint32_t ent[kHeadsPerCluster][kUnits] = {};
  int uses[kSlots] = {};
  for (int i = 0; i < kHeadsPerCluster * kUnits; i++) {
    int sl = i;
    if (i >= kSlots) {
      int k = i - kSlots;
      const int v = i - (kHeadsPerCluster - 1) * kUnits - 18;
      if (v >= 0) k = (kHeadsPerCluster - 1) * kUnits + kLastV[v];
      const int prev = (k / kUnits) * kUnits + rel[k % kUnits];
      sl = slot[prev];
      ent[prev / kUnits][prev % kUnits] |= 32u;
    }
    slot[i] = sl;
    const int h = i / kUnits, u = i % kUnits;
    ent[h][u] = (uint32_t)(sl | ((uses[sl] & 1) << 4));
    uses[sl]++;
    int kind = 0, cb = 0, r64 = 0;
    if (u < 2 || (u >= 6 && u < 10)) {
      cb = (u & 1) * 2;
      r64 = u < 2 ? 0 : (u - 4) / 2;
    } else if (u < 18) {
      const int ku = u < 6 ? u - 2 : u - 6;
      kind = 1, cb = ku & 3, r64 = (ku / 4) * 2;
    } else {
      kind = 2, cb = (u - 18) / 3, r64 = ((u - 18) % 3) * 2;
    }
    s.prod[i] = (ent[h][u] & 31u) | (uint32_t)(kind << 5) | (uint32_t)(cb << 8) | (uint32_t)((h * kClusters * 6 + r64) << 12);
  }
  for (int h = 0; h < kHeadsPerCluster; h++) {
    for (int g = 0; g < 3; g++)
      for (int a = 0; a < 4; a++) s.cons[h][g] |= ent[h][kIdx(g * 4 + a)] << (8 * a);
    for (int c = 0; c < 4; c++)
      for (int a = 0; a < 3; a++) s.cons[h][3 + c] |= ent[h][18 + c * 3 + a] << (8 * a);
    for (int w = 0; w < 3; w++)
      for (int a = 0; a < 2; a++) s.cons[h][8 + w] |= ent[h][qIdx(w, a)] << (8 * a);
  }
  return s;
}
__constant__ Sched c_sched = makeSched();

__device__ __forceinline__ uint32_t smem_u32(const void* p) { return (uint32_t)__cvta_generic_to_shared(p); }
__device__ __forceinline__ void mbar_init(uint32_t bar, uint32_t cnt) {
  asm volatile("mbarrier.init.shared::cta.b64 [%0], %1;" ::"r"(bar), "r"(cnt) : "memory");
}
__device__ __forceinline__ void mbar_expect_tx(uint32_t bar, uint32_t bytes) {
  asm volatile("mbarrier.arrive.expect_tx.shared::cta.b64 _, [%0], %1;" ::"r"(bar), "r"(bytes) : "memory");
}
__device__ __forceinline__ void mbar_wait(uint32_t bar, uint32_t parity) {
  asm volatile(
      "{\n"
      ".reg .pred p;\n"
      ".reg .u32 n;\n"
      "mov.u32 n, 0;\n"
      "LAB_WAIT:\n"
      "mbarrier.try_wait.parity.shared::cta.b64 p, [%0], %1;\n"
      "@p bra LAB_DONE;\n"
      "add.u32 n, n, 1;\n"
      "setp.lt.u32 p, n, 0x400000;\n"
      "@p bra LAB_WAIT;\n"
      "trap;\n"
      "LAB_DONE:\n"
      "}\n" ::"r"(bar),
      "r"(parity)
      : "memory");
}
__device__ __forceinline__ bool mbar_test(uint32_t bar, uint32_t parity) {
  uint32_t ok;
  asm volatile("{\n.reg .pred p;\nmbarrier.test_wait.parity.shared::cta.b64 p, [%1], %2;\nselp.u32 %0, 1, 0, p;\n}\n"
               : "=r"(ok)
               : "r"(bar), "r"(parity)
               : "memory");
  return ok;
}
__device__ __forceinline__ uint32_t map_to_cta(uint32_t addr, uint32_t cta) {
  uint32_t r;
  asm("mapa.shared::cluster.u32 %0, %1, %2;" : "=r"(r) : "r"(addr), "r"(cta));
  return r;
}
__device__ __forceinline__ void release_slot(uint32_t bars, uint32_t entry, uint32_t lane, uint32_t count) {
  asm volatile(
      "{\n"
      ".reg .pred p;\n"
      "setp.lt.u32 p, %1, %3;\n"
      "@p mbarrier.arrive.shared::cluster.b64 _, [%0], %2;\n"
      "}\n" ::"r"(bars + 8 * (entry & 15u)),
      "r"(lane), "r"(count), "r"((entry >> 4) & 2u)
      : "memory");
}
__device__ __forceinline__ void tma_load(uint32_t dst, const CUtensorMap* m, uint32_t bar, int row, int cb, uint64_t pol) {
  asm volatile(
      "{\n.reg .pred p;\nelect.sync _|p, 0xffffffff;\n"
      "@p mbarrier.arrive.expect_tx.shared::cta.b64 _, [%2], 16384;\n"
      "@p cp.async.bulk.tensor.3d.shared::cluster.global.mbarrier::complete_tx::bytes.L2::cache_hint [%0], [%1, {%3, %4, %5}], [%2], %6;\n}\n" ::"r"(dst),
      "l"(m), "r"(bar), "r"(0), "r"(row), "r"(cb), "l"(pol)
      : "memory");
}
__device__ __forceinline__ void tma_load_mc(uint32_t dst, const CUtensorMap* m, uint32_t bar, int row, int cb, uint64_t pol) {
  asm volatile(
      "{\n.reg .pred p;\nelect.sync _|p, 0xffffffff;\n"
      "@p mbarrier.arrive.expect_tx.shared::cta.b64 _, [%2], 16384;\n"
      "@p cp.async.bulk.tensor.3d.shared::cluster.global.mbarrier::complete_tx::bytes.multicast::cluster.L2::cache_hint [%0], [%1, {%3, %4, "
      "%5}], [%2], %6, %7;\n}\n" ::"r"(dst),
      "l"(m), "r"(bar), "r"(0), "r"(row), "r"(cb), "h"((uint16_t)3), "l"(pol)
      : "memory");
}
__device__ __forceinline__ void tma_prefetch(const CUtensorMap* m, int row, int cb) {
  asm volatile(
      "{\n.reg .pred p;\nelect.sync _|p, 0xffffffff;\n"
      "@p cp.async.bulk.prefetch.tensor.3d.L2.global [%0, {%1, %2, %3}];\n}\n" ::"l"(m), "r"(0), "r"(row), "r"(cb)
      : "memory");
}
__device__ __forceinline__ void cluster_arrive() { asm volatile("barrier.cluster.arrive.relaxed.aligned;" ::: "memory"); }
__device__ __forceinline__ void cluster_wait() { asm volatile("barrier.cluster.wait.aligned;" ::: "memory"); }
__device__ __forceinline__ void turn_wait(int id) { asm volatile("bar.sync %0, 256;" ::"r"(id) : "memory"); }
__device__ __forceinline__ void turn_pass(int id) { asm volatile("bar.arrive %0, 256;" ::"r"(id) : "memory"); }
__device__ __forceinline__ void wg_fence() { asm volatile("wgmma.fence.sync.aligned;" ::: "memory"); }
__device__ __forceinline__ void wg_commit() { asm volatile("wgmma.commit_group.sync.aligned;" ::: "memory"); }
template <int N>
__device__ __forceinline__ void wg_wait() {
  asm volatile("wgmma.wait_group.sync.aligned %0;" ::"n"(N) : "memory");
}
__device__ __forceinline__ float ex2(float x) {
  float y;
  asm("ex2.approx.ftz.f32 %0, %1;" : "=f"(y) : "f"(x));
  return y;
}
__device__ __forceinline__ uint32_t pack_bf16(float lo, float hi) {
  uint32_t r;
  asm("cvt.rn.bf16x2.f32 %0, %1, %2;" : "=r"(r) : "f"(hi), "f"(lo));
  return r;
}
__device__ __forceinline__ void scale_bf16x2(uint32_t& x, uint32_t fh, uint32_t fl) {
  asm("{\n.reg .b32 t;\nmul.rn.bf16x2 t, %0, %2;\nfma.rn.bf16x2 %0, %0, %1, t;\n}\n" : "+r"(x) : "r"(fh), "r"(fl));
}
__device__ __forceinline__ float rcp(float x) {
  float y;
  asm("rcp.approx.ftz.f32 %0, %1;" : "=f"(y) : "f"(x));
  return y;
}

constexpr uint32_t kDescHi = 64u | (1u << 30);
__device__ __forceinline__ uint32_t desc_lo(uint32_t addr) { return ((addr & 0x3FFFF) >> 4) | (1u << 16); }

#define ACC8(a, o) \
  "+f"(a[o]), "+f"(a[o + 1]), "+f"(a[o + 2]), "+f"(a[o + 3]), "+f"(a[o + 4]), "+f"(a[o + 5]), "+f"(a[o + 6]), "+f"(a[o + 7])
#define IN8(a, o) \
  "r"(a[o]), "r"(a[o + 1]), "r"(a[o + 2]), "r"(a[o + 3]), "r"(a[o + 4]), "r"(a[o + 5]), "r"(a[o + 6]), "r"(a[o + 7])
#define REGS32 "{%0,%1,%2,%3,%4,%5,%6,%7,%8,%9,%10,%11,%12,%13,%14,%15,%16,%17,%18,%19,%20,%21,%22,%23,%24,%25,%26,%27,%28,%29,%30,%31}"
#define REGS64 "{%0,%1,%2,%3,%4,%5,%6,%7,%8,%9,%10,%11,%12,%13,%14,%15,%16,%17,%18,%19,%20,%21,%22,%23,%24,%25,%26,%27,%28,%29,%30,%31,%32,%33,%34,%35,%36,%37,%38,%39,%40,%41,%42,%43,%44,%45,%46,%47,%48,%49,%50,%51,%52,%53,%54,%55,%56,%57,%58,%59,%60,%61,%62,%63}"

__device__ __forceinline__ void mma_qk(float (&d)[64], uint32_t qa, uint32_t kb, int accumulate) {
  asm volatile(
      "{\n.reg .pred p;\n.reg .b32 a, b;\n.reg .b64 da, db;\n"
      "setp.ne.b32 p, %66, 0;\n"
      "mov.b64 da, {%64, %67};\nmov.b64 db, {%65, %67};\n"
      "wgmma.mma_async.sync.aligned.m64n128k16.f32.bf16.bf16 " REGS64 ", da, db, p, 1, 1, 0, 0;\n"
      "add.u32 a, %64, 2;\nadd.u32 b, %65, 2;\nmov.b64 da, {a, %67};\nmov.b64 db, {b, %67};\n"
      "wgmma.mma_async.sync.aligned.m64n128k16.f32.bf16.bf16 " REGS64 ", da, db, 1, 1, 1, 0, 0;\n"
      "add.u32 a, %64, 4;\nadd.u32 b, %65, 4;\nmov.b64 da, {a, %67};\nmov.b64 db, {b, %67};\n"
      "wgmma.mma_async.sync.aligned.m64n128k16.f32.bf16.bf16 " REGS64 ", da, db, 1, 1, 1, 0, 0;\n"
      "add.u32 a, %64, 6;\nadd.u32 b, %65, 6;\nmov.b64 da, {a, %67};\nmov.b64 db, {b, %67};\n"
      "wgmma.mma_async.sync.aligned.m64n128k16.f32.bf16.bf16 " REGS64 ", da, db, 1, 1, 1, 0, 0;\n"
      "wgmma.commit_group.sync.aligned;\n}\n"
      : ACC8(d, 0), ACC8(d, 8), ACC8(d, 16), ACC8(d, 24), ACC8(d, 32), ACC8(d, 40), ACC8(d, 48), ACC8(d, 56)
      : "r"(qa), "r"(kb), "r"(accumulate), "n"(kDescHi)
      : "memory");
}
__device__ __forceinline__ void mma_pv(float (&d)[32], const uint32_t* a, uint32_t vb, int accumulate) {
  asm volatile(
      "{\n.reg .pred p;\n.reg .b32 b;\n.reg .b64 db;\n"
      "setp.ne.b32 p, %65, 0;\n"
      "mov.b64 db, {%64, %66};\n"
      "wgmma.mma_async.sync.aligned.m64n64k16.f32.bf16.bf16 " REGS32 ", {%32,%33,%34,%35}, db, p, 1, 1, 1;\n"
      "add.u32 b, %64, 128;\nmov.b64 db, {b, %66};\n"
      "wgmma.mma_async.sync.aligned.m64n64k16.f32.bf16.bf16 " REGS32 ", {%36,%37,%38,%39}, db, 1, 1, 1, 1;\n"
      "add.u32 b, %64, 256;\nmov.b64 db, {b, %66};\n"
      "wgmma.mma_async.sync.aligned.m64n64k16.f32.bf16.bf16 " REGS32 ", {%40,%41,%42,%43}, db, 1, 1, 1, 1;\n"
      "add.u32 b, %64, 384;\nmov.b64 db, {b, %66};\n"
      "wgmma.mma_async.sync.aligned.m64n64k16.f32.bf16.bf16 " REGS32 ", {%44,%45,%46,%47}, db, 1, 1, 1, 1;\n"
      "add.u32 b, %64, 512;\nmov.b64 db, {b, %66};\n"
      "wgmma.mma_async.sync.aligned.m64n64k16.f32.bf16.bf16 " REGS32 ", {%48,%49,%50,%51}, db, 1, 1, 1, 1;\n"
      "add.u32 b, %64, 640;\nmov.b64 db, {b, %66};\n"
      "wgmma.mma_async.sync.aligned.m64n64k16.f32.bf16.bf16 " REGS32 ", {%52,%53,%54,%55}, db, 1, 1, 1, 1;\n"
      "add.u32 b, %64, 768;\nmov.b64 db, {b, %66};\n"
      "wgmma.mma_async.sync.aligned.m64n64k16.f32.bf16.bf16 " REGS32 ", {%56,%57,%58,%59}, db, 1, 1, 1, 1;\n"
      "add.u32 b, %64, 896;\nmov.b64 db, {b, %66};\n"
      "wgmma.mma_async.sync.aligned.m64n64k16.f32.bf16.bf16 " REGS32 ", {%60,%61,%62,%63}, db, 1, 1, 1, 1;\n"
      "wgmma.commit_group.sync.aligned;\n}\n"
      : ACC8(d, 0), ACC8(d, 8), ACC8(d, 16), ACC8(d, 24)
      : IN8(a, 0), IN8(a, 8), IN8(a, 16), IN8(a, 24), "r"(vb), "r"(accumulate), "n"(kDescHi)
      : "memory");
}
template <int N>
__device__ __forceinline__ void keep_regs(float (&d)[N]) {
#pragma unroll
  for (int i = 0; i < N; i++) asm volatile("" : "+f"(d[i])::"memory");
}

__device__ __forceinline__ uint4 quad_transpose(uint32_t a0, uint32_t a1, uint32_t a2, uint32_t a3, bool b0, bool b1) {
  uint32_t s0 = b0 ? a0 : a1, s1 = b0 ? a2 : a3;
  uint32_t r0 = __shfl_xor_sync(0xffffffffu, s0, 1), r1 = __shfl_xor_sync(0xffffffffu, s1, 1);
  uint32_t c0 = b0 ? r0 : a0, c1 = b0 ? a1 : r0, c2 = b0 ? r1 : a2, c3 = b0 ? a3 : r1;
  uint32_t t0 = b1 ? c0 : c2, t1 = b1 ? c1 : c3;
  uint32_t u0 = __shfl_xor_sync(0xffffffffu, t0, 2), u1 = __shfl_xor_sync(0xffffffffu, t1, 2);
  uint4 r;
  r.x = b1 ? u0 : c0;
  r.y = b1 ? u1 : c1;
  r.z = b1 ? c2 : u0;
  r.w = b1 ? c3 : u1;
  return r;
}

constexpr float kScaleLog2 = 0.0625f * 1.4426950408889634f;

#define LAZY 1
#define IMAX 1
constexpr float kRescaleThreshold = 8.f;

template <int N>
__device__ __forceinline__ void rescale_p(uint32_t* P, float f0, float f1) {
  const uint32_t h0 = pack_bf16(f0, f0), h1 = pack_bf16(f1, f1);
  const float r0 = f0 - __uint_as_float(h0 << 16), r1 = f1 - __uint_as_float(h1 << 16);
  const uint32_t l0 = pack_bf16(r0, r0), l1 = pack_bf16(r1, r1);
#pragma unroll
  for (int i = 0; i < N / 2; i++) {
    scale_bf16x2(P[2 * i], h0, l0);
    scale_bf16x2(P[2 * i + 1], h1, l1);
  }
}

__device__ __forceinline__ void row_max_float(const float (&s)[64], float& mx0, float& mx1) {
  mx0 = fmaxf(s[0], s[1]), mx1 = fmaxf(s[2], s[3]);
#pragma unroll
  for (int i = 1; i < 16; i++) {
    mx0 = fmaxf(mx0, fmaxf(s[4 * i], s[4 * i + 1]));
    mx1 = fmaxf(mx1, fmaxf(s[4 * i + 2], s[4 * i + 3]));
  }
  mx0 = fmaxf(mx0, __shfl_xor_sync(0xffffffffu, mx0, 1));
  mx1 = fmaxf(mx1, __shfl_xor_sync(0xffffffffu, mx1, 1));
  mx0 = fmaxf(mx0, __shfl_xor_sync(0xffffffffu, mx0, 2));
  mx1 = fmaxf(mx1, __shfl_xor_sync(0xffffffffu, mx1, 2));
}
__device__ __forceinline__ void row_max_int(const float (&s)[64], float& mx0, float& mx1) {
  int a0 = max(__float_as_int(s[0]), __float_as_int(s[1])), a1 = max(__float_as_int(s[2]), __float_as_int(s[3]));
  int b0 = max(__float_as_int(s[4]), __float_as_int(s[5])), b1 = max(__float_as_int(s[6]), __float_as_int(s[7]));
#pragma unroll
  for (int i = 1; i < 8; i++) {
    a0 = __vimax3_s32(a0, __float_as_int(s[8 * i]), __float_as_int(s[8 * i + 1]));
    a1 = __vimax3_s32(a1, __float_as_int(s[8 * i + 2]), __float_as_int(s[8 * i + 3]));
    b0 = __vimax3_s32(b0, __float_as_int(s[8 * i + 4]), __float_as_int(s[8 * i + 5]));
    b1 = __vimax3_s32(b1, __float_as_int(s[8 * i + 6]), __float_as_int(s[8 * i + 7]));
  }
  a0 = max(a0, b0);
  a1 = max(a1, b1);
  a0 = max(a0, __shfl_xor_sync(0xffffffffu, a0, 1));
  a1 = max(a1, __shfl_xor_sync(0xffffffffu, a1, 1));
  a0 = max(a0, __shfl_xor_sync(0xffffffffu, a0, 2));
  a1 = max(a1, __shfl_xor_sync(0xffffffffu, a1, 2));
  mx0 = __int_as_float(a0);
  mx1 = __int_as_float(a1);
}

template <int J>
__device__ __forceinline__ void softmax_chunk(float (&s)[64], uint32_t (&P)[96], float (&m)[2], float (&l)[2],
                                              float (&mh)[2][2]) {
  float mx0, mx1;
  row_max_int(s, mx0, mx1);
  bool redo = (__float_as_int(mx0) | __float_as_int(mx1)) < 0;
  if (J > 0) redo = redo || fmaf(mx0, kScaleLog2, -m[0]) > kRescaleThreshold || fmaf(mx1, kScaleLog2, -m[1]) > kRescaleThreshold;
  if ((IMAX || J > 0) && __any_sync(0xffffffffu, redo)) {
    if (IMAX) row_max_float(s, mx0, mx1);
    if (J > 0) {
      const float n0 = fmaxf(m[0], mx0 * kScaleLog2), n1 = fmaxf(m[1], mx1 * kScaleLog2);
      const float f0 = ex2(m[0] - n0), f1 = ex2(m[1] - n1);
      rescale_p<32 * J>(P, f0, f1);
      l[0] *= f0, l[1] *= f1;
      m[0] = n0, m[1] = n1;
    }
  }
  if (J == 0) m[0] = mx0 * kScaleLog2, m[1] = mx1 * kScaleLog2;
  float a0 = J ? l[0] : 0.f, a1 = J ? l[1] : 0.f, b0 = 0.f, b1 = 0.f;
#pragma unroll
  for (int ii = 0; ii < 16; ii++) {
    const int i = LAZY ? ii ^ 8 : ii;
    s[4 * i] = ex2(fmaf(s[4 * i], kScaleLog2, -m[0]));
    s[4 * i + 1] = ex2(fmaf(s[4 * i + 1], kScaleLog2, -m[0]));
    s[4 * i + 2] = ex2(fmaf(s[4 * i + 2], kScaleLog2, -m[1]));
    s[4 * i + 3] = ex2(fmaf(s[4 * i + 3], kScaleLog2, -m[1]));
    a0 += s[4 * i];
    b0 += s[4 * i + 1];
    a1 += s[4 * i + 2];
    b1 += s[4 * i + 3];
    P[32 * J + 2 * i] = pack_bf16(s[4 * i], s[4 * i + 1]);
    P[32 * J + 2 * i + 1] = pack_bf16(s[4 * i + 2], s[4 * i + 3]);
  }
  l[0] = a0 + b0;
  l[1] = a1 + b1;
}

constexpr int kIssuers = PACE > 0 ? 3 : 4;
constexpr uint32_t kTicks = kHeadsPerCluster * kUnits / 3;
__device__ unsigned int g_ticks;

__global__ void __cluster_dims__(2, 1, 1) __launch_bounds__(kThreads, 1)
    mha_kernel(const __grid_constant__ CUtensorMap mapQ, const __grid_constant__ CUtensorMap mapK,
               const __grid_constant__ CUtensorMap mapV, const char* __restrict__ gq, const char* __restrict__ gk,
               const char* __restrict__ gv, __nv_bfloat16* __restrict__ out) {
  extern __shared__ unsigned char smem_raw[];
  const uint32_t base = (smem_u32(smem_raw) + 1023u) & ~1023u;
  const uint32_t bar_full = base + kSlots * kSlotBytes;
  const uint32_t bar_empty = bar_full + 128;
  const int wg = __shfl_sync(0xffffffffu, (int)(threadIdx.x >> 7), 0);
  const int rank = blockIdx.x & 1;
  const int cid = blockIdx.x >> 1;

  const uint32_t t_entry = clock();
  if (threadIdx.x == 384) {
    asm volatile("prefetch.tensormap [%0];" ::"l"(&mapQ) : "memory");
    asm volatile("prefetch.tensormap [%0];" ::"l"(&mapK) : "memory");
    asm volatile("prefetch.tensormap [%0];" ::"l"(&mapV) : "memory");
  }
#define WARM 8
  if (WARM == 1 && threadIdx.x >= 416 && threadIdx.x < 419) {
    const char* g = threadIdx.x == 416 ? gq + rank * 98304 : threadIdx.x == 417 ? gk + rank * 32768 : gv + rank * 32768;
    asm volatile("prefetch.global.L2 [%0];" ::"l"(g + (size_t)cid * (kSeq * 512)) : "memory");
  }
  if (WARM >= 2 && cid < WARM) {
    const size_t off = (size_t)cid * (kSeq * 512);
    asm volatile("prefetch.global.L2 [%0];" ::"l"(gq + off + rank * 98304 + threadIdx.x * 128) : "memory");
    asm volatile("prefetch.global.L2 [%0];" ::"l"(gk + off + rank * 65536 + threadIdx.x * 128) : "memory");
    if (threadIdx.x < 256) asm volatile("prefetch.global.L2 [%0];" ::"l"(gq + off + rank * 98304 + 65536 + threadIdx.x * 128) : "memory");
  } else if (WARM >= 2 && threadIdx.x >= 416 && threadIdx.x < 419) {
    const char* g = threadIdx.x == 416 ? gq + rank * 98304 : threadIdx.x == 417 ? gk + rank * 32768 : gv + rank * 32768;
    asm volatile("prefetch.global.L2 [%0];" ::"l"(g + (size_t)cid * (kSeq * 512)) : "memory");
  }
  if (threadIdx.x < kSlots) {
    mbar_init(bar_full + 8 * threadIdx.x, 1);
    mbar_init(bar_empty + 8 * threadIdx.x, kEmptyCount);
    asm volatile("fence.mbarrier_init.release.cluster;" ::: "memory");
  }
  if (PACE > 0 && threadIdx.x == 32) asm volatile("st.shared.v2.u32 [%0], {%1, %1};" ::"r"(bar_full + 256), "r"(0) : "memory");
  __syncthreads();
  cluster_arrive();

  if (wg == 3) {
    asm volatile("setmaxnreg.dec.sync.aligned.u32 32;");
    const int pw = __shfl_sync(0xffffffffu, (int)(threadIdx.x >> 5) & 3, 0);
    if (pw >= 2) cluster_wait();
    const uint32_t pace_word = bar_full + 256;
    if (PACE > 0 && pw == 3) {
      if (rank == 0) {
#pragma unroll 1
        for (int n = 0; n < (1 << 16); n++) {
          uint32_t seen, done;
          asm volatile("ld.relaxed.gpu.global.u32 %0, [%1];" : "=r"(seen) : "l"(&g_ticks) : "memory");
          asm volatile("st.volatile.shared.u32 [%0], %1;" ::"r"(pace_word), "r"(seen) : "memory");
          asm volatile("ld.volatile.shared.u32 %0, [%1];" : "=r"(done) : "r"(pace_word + 4) : "memory");
          if (done) break;
          __nanosleep(100);
        }
      }
    } else {
      const bool pacer = PACE > 0 && pw == 0 && rank == 0;
      const int head_start = max(kClusters / 2 - cid, 0) * POFF / 16;
      int mine = 0, tick = 0;
      if (DELTA > 0) {
        while ((uint32_t)clock() - t_entry < (uint32_t)(max(cid - DSKIP, 0) * DELTA)) {
          __nanosleep(20);
        }
      }
      uint64_t pol_first, pol_normal;
      asm volatile("createpolicy.fractional.L2::evict_first.b64 %0, 1.0;" : "=l"(pol_first));
      asm volatile("createpolicy.fractional.L2::evict_normal.b64 %0, 1.0;" : "=l"(pol_normal));
#pragma unroll 1
      for (int i = pw; i < kHeadsPerCluster * kUnits; i += kIssuers) {
        const uint32_t e = c_sched.prod[i];
        const uint32_t sl = e & 15u, kind = (e >> 5) & 3u;
        const uint32_t dst = base + sl * kSlotBytes, fb = bar_full + 8 * sl;
        const int row = (int)(e >> 12) * 64 + cid * kSeq, cb = (e >> 8) & 3u;
        if (PFN > 0 && i >= kSlots && i < kSlots + kIssuers) {
#pragma unroll 1
          for (int k = i; k < kSlots + PFN; k += kIssuers) {
            const uint32_t ek = c_sched.prod[k];
            tma_prefetch(((ek >> 5) & 3u) == 1 ? &mapK : &mapV, (int)(ek >> 12) * 64 + cid * kSeq + rank * 64, (ek >> 8) & 3u);
          }
        }
        mbar_wait(bar_empty + 8 * sl, ((e >> 4) & 1u) ^ 1u);
        if (pacer) {
#pragma unroll 1
          for (int n = 0; n < 256; n++) {
            uint32_t seen;
            asm volatile("ld.volatile.shared.u32 %0, [%1];" : "=r"(seen) : "r"(pace_word) : "memory");
            if (mine - (int)seen <= PACE + head_start * max(PEND - tick, 0) / PEND) break;
            __nanosleep(40);
          }
          mine += kClusters, tick++;
        }
        const uint64_t pol = i >= EFU ? pol_first : pol_normal;
        if (kind == 0) tma_load(dst, &mapQ, fb, row + rank * 192, cb, pol);
        else tma_load_mc(dst + rank * 8192, kind == 1 ? &mapK : &mapV, fb, row + rank * 64, cb, pol);
        if (i < 2) cluster_wait();
        if (pacer && (threadIdx.x & 31) == 0)
          asm volatile("red.relaxed.gpu.global.inc.u32 [%0], %1;" ::"l"(&g_ticks), "r"(kTicks * kClusters - 1) : "memory");
      }
      if (pacer) asm volatile("st.volatile.shared.u32 [%0], %1;" ::"r"(pace_word + 4), "r"(1) : "memory");
    }
  } else {
    asm volatile("setmaxnreg.inc.sync.aligned.u32 160;");
    const uint32_t lane = threadIdx.x & 31;
    const uint32_t dbase = desc_lo(base);
    const uint32_t rel_bar = map_to_cta(bar_empty, lane & 1);
    const int my_turn = 1 + wg, next_turn = 1 + (wg == 2 ? 0 : wg + 1);
    cluster_wait();
    if (wg == 2) turn_pass(1);
    const bool b0 = lane & 1, b1 = lane & 2;
    const uint32_t out_off =
        (uint32_t)(rank * 192 + wg * 64 + ((threadIdx.x >> 5) & 3) * 16 + (lane >> 2)) * 512u + (lane & 3) * 16u;

#pragma unroll 1
    for (int h = 0; h < kHeadsPerCluster; h++) {
      uint32_t P[96];
      float m[2], l[2], mh[2][2];
      const uint32_t qw = c_sched.cons[h][8 + wg];
      const uint32_t q0 = qw & 15u, q1 = (qw >> 8) & 15u;

      auto qk_chunk = [&](auto jc) {
        constexpr int j = decltype(jc)::value;
        float s[64];
        const uint32_t kw = c_sched.cons[h][j];
        if (j == 0) mbar_wait(bar_full + 8 * q0, (qw >> 4) & 1u);
        mbar_wait(bar_full + 8 * (kw & 15u), (kw >> 4) & 1u);
        turn_wait(my_turn);
        wg_fence();
#pragma unroll
        for (int cb = 0; cb < 4; cb++) {
          const uint32_t e = kw >> (8 * cb), en = e >> 8;
          bool ready = true;
          if (cb < 3) ready = mbar_test(bar_full + 8 * (en & 15u), (en >> 4) & 1u);
          if (j == 0 && cb == 1) ready = ready && mbar_test(bar_full + 8 * q1, (qw >> 12) & 1u);
          mma_qk(s, dbase + (cb < 2 ? q0 : q1) * 1024 + (cb & 1) * 512, dbase + (e & 15u) * 1024, cb != 0);
          if (cb > 0) {
            wg_wait<1>();
            if (cb == 3) turn_pass(next_turn);
            release_slot(rel_bar, kw >> (8 * cb - 8), lane, 1);
            if (j == 2 && cb == 2) release_slot(rel_bar, qw, lane, 3);
          }
          if (!ready) {
            if (j == 0 && cb == 1) mbar_wait(bar_full + 8 * q1, (qw >> 12) & 1u);
            mbar_wait(bar_full + 8 * (en & 15u), (en >> 4) & 1u);
          }
        }
        wg_wait<0>();
        keep_regs(s);
        release_slot(rel_bar, kw >> 24, lane, 1);
        if (j == 2) release_slot(rel_bar, qw >> 8, lane, 3);
        softmax_chunk<j>(s, P, m, l, mh);
      };
      qk_chunk(std::integral_constant<int, 0>{});
      qk_chunk(std::integral_constant<int, 1>{});
      qk_chunk(std::integral_constant<int, 2>{});
      l[0] += __shfl_xor_sync(0xffffffffu, l[0], 1);
      l[1] += __shfl_xor_sync(0xffffffffu, l[1], 1);
      l[0] += __shfl_xor_sync(0xffffffffu, l[0], 2);
      l[1] += __shfl_xor_sync(0xffffffffu, l[1], 2);
      const float inv0 = rcp(l[0]), inv1 = rcp(l[1]);

      char* optr = reinterpret_cast<char*>(out) + (size_t)(cid + h * kClusters) * (kSeq * 512) + out_off;
#pragma unroll 1
      for (int c = 0; c < 4; c++) {
        float o[32];
        const uint32_t vw = c_sched.cons[h][3 + c];
        mbar_wait(bar_full + 8 * (vw & 15u), (vw >> 4) & 1u);
        turn_wait(my_turn);
        wg_fence();
#pragma unroll
        for (int j = 0; j < 3; j++) {
          const uint32_t e = vw >> (8 * j), en = e >> 8;
          bool ready = true;
          if (j < 2) ready = mbar_test(bar_full + 8 * (en & 15u), (en >> 4) & 1u);
          mma_pv(o, P + 32 * j, dbase + (e & 15u) * 1024, j != 0);
          if (j > 0) {
            wg_wait<1>();
            if (j == 2 && !(wg == 2 && c == 3 && h == kHeadsPerCluster - 1)) turn_pass(next_turn);
            release_slot(rel_bar, vw >> (8 * j - 8), lane, 1);
          }
          if (!ready) mbar_wait(bar_full + 8 * (en & 15u), (en >> 4) & 1u);
        }
        wg_wait<0>();
        keep_regs(o);
        release_slot(rel_bar, vw >> 16, lane, 1);
#pragma unroll
        for (int q = 0; q < 2; q++) {
#pragma unroll
          for (int r = 0; r < 2; r++) {
            const int b = 16 * q + 2 * r;
            const float f = r ? inv1 : inv0;
            const uint4 v = quad_transpose(pack_bf16(o[b] * f, o[b + 1] * f), pack_bf16(o[b + 4] * f, o[b + 5] * f),
                                           pack_bf16(o[b + 8] * f, o[b + 9] * f), pack_bf16(o[b + 12] * f, o[b + 13] * f), b0, b1);
            *reinterpret_cast<uint4*>(optr + r * 4096 + q * 64) = v;
          }
        }
        optr += 128;
      }
    }
  }
}

typedef CUresult (*EncodeTiledFn)(CUtensorMap*, CUtensorMapDataType, cuuint32_t, void*, const cuuint64_t*,
                                  const cuuint64_t*, const cuuint32_t*, const cuuint32_t*, CUtensorMapInterleave,
                                  CUtensorMapSwizzle, CUtensorMapL2promotion, CUtensorMapFloatOOBfill);

CUtensorMap make_map(EncodeTiledFn enc, const void* ptr, uint32_t boxBlocks) {
  CUtensorMap m;
  cuuint64_t dims[3] = {64, (cuuint64_t)kHeads * kSeq, 4};
  cuuint64_t strides[2] = {512, 128};
  cuuint32_t box[3] = {64, 64, boxBlocks};
  cuuint32_t es[3] = {1, 1, 1};
  enc(&m, CU_TENSOR_MAP_DATA_TYPE_BFLOAT16, 3, const_cast<void*>(ptr), dims, strides, box, es,
      CU_TENSOR_MAP_INTERLEAVE_NONE, CU_TENSOR_MAP_SWIZZLE_128B, CU_TENSOR_MAP_L2_PROMOTION_L2_128B,
      CU_TENSOR_MAP_FLOAT_OOB_FILL_NONE);
  return m;
}

}

extern "C" void kernel_launch(void* const* d_in, const int* in_sizes, int n_in, void* d_out, int out_size) {
  static EncodeTiledFn enc = nullptr;
  if (!enc) {
    void* fn = nullptr;
    cudaDriverEntryPointQueryResult qr;
    cudaGetDriverEntryPoint("cuTensorMapEncodeTiled", &fn, cudaEnableDefault, &qr);
    enc = (EncodeTiledFn)fn;
    cudaFuncSetAttribute(mha_kernel, cudaFuncAttributeMaxDynamicSharedMemorySize, kSmemBytes);
  }
  const CUtensorMap mq = make_map(enc, d_in[0], 2);
  const CUtensorMap mk = make_map(enc, d_in[1], 1);
  const CUtensorMap mv = make_map(enc, d_in[2], 1);
  mha_kernel<<<2 * kClusters, kThreads, kSmemBytes, cudaStreamPerThread>>>(mq, mk, mv, (const char*)d_in[0], (const char*)d_in[1],
                                                                            (const char*)d_in[2], (__nv_bfloat16*)d_out);
}
```

```cpp
#include <cuda_runtime.h>
#include <cuda_bf16.h>
#include <cuda.h>
#include <stdint.h>
#include <type_traits>

namespace {

constexpr int kSeq = 384;
constexpr int kHeads = 512;
constexpr int kHeadBytes = kSeq * 512;
constexpr int kClusters = 64;
constexpr int kRounds = kHeads / kClusters;
constexpr int kSlots = 14;
constexpr int kSlotBytes = 16384;
constexpr int kUnits = 30;
constexpr int kLoads = kRounds * kUnits;
constexpr int kThreads = 512;
constexpr int kSmemBytes = kSlots * kSlotBytes + 1024   + 1024  ;
constexpr uint32_t kEmptyCount = 24;

constexpr int kIssuers = 3;
constexpr int kWarmClusters = 8;
constexpr int kStaggerClocks = 225;
constexpr int kStreamFrom = 190;
constexpr int kTicks = kLoads / kIssuers;
constexpr int kLeadEnd = 105;
constexpr int kLeadExtra = 130;
constexpr int kFadeBegin = 40, kFadeEnd = 70;

constexpr int kIdx(int u) { return u < 4 ? 2 + u : 6 + u; }
constexpr int qIdx(int w, int h) { return w == 0 ? h : 4 + 2 * w + h; }
struct Sched {
  uint32_t cons[kRounds][12];
  uint32_t prod[kLoads];
};
constexpr Sched makeSched() {
  Sched s{};
  int rel[kUnits] = {};
  int n = 0;
  for (int g = 0; g < 3; g++)
    for (int w = 0; w < 3; w++)
      for (int a = 0; a < 4; a++) {
        if (w == 2) rel[n++] = kIdx(g * 4 + a);
        if (g == 2 && (a & 1)) rel[n++] = qIdx(w, a / 2);
      }
  for (int x = 0; x < 12; x++) rel[n++] = 18 + x;
  const int last_v[12] = {4, 5, 6, 8, 9, 10, 12, 13, 15, 18, 19, 20};
  int slot[kLoads] = {};
  uint32_t ent[kRounds][kUnits] = {};
  int uses[kSlots] = {};
  for (int i = 0; i < kLoads; i++) {
    const int h = i / kUnits, u = i % kUnits;
    int sl = i;
    if (i >= kSlots) {
      const int k = (h == kRounds - 1 && u >= 18) ? h * kUnits + last_v[u - 18] : i - kSlots;
      const int prev = (k / kUnits) * kUnits + rel[k % kUnits];
      sl = slot[prev];
      ent[prev / kUnits][prev % kUnits] |= 32u;
    }
    slot[i] = sl;
    ent[h][u] = (uint32_t)(sl | ((uses[sl]++ & 1) << 4));
    int kind = 0, cb = 0, r64 = 0;
    if (u < 2 || (u >= 6 && u < 10)) {
      cb = (u & 1) * 2, r64 = u < 2 ? 0 : (u - 4) / 2;
    } else if (u < 18) {
      const int ku = u < 6 ? u - 2 : u - 6;
      kind = 1, cb = ku & 3, r64 = (ku / 4) * 2;
    } else {
      kind = 2, cb = (u - 18) / 3, r64 = ((u - 18) % 3) * 2;
    }
    s.prod[i] = ent[h][u] | (uint32_t)(kind << 5) | (uint32_t)(cb << 8) | (uint32_t)((h * kClusters * 6 + r64) << 12);
  }
  for (int h = 0; h < kRounds; h++) {
    for (int g = 0; g < 3; g++)
      for (int a = 0; a < 4; a++) s.cons[h][g] |= ent[h][kIdx(g * 4 + a)] << (8 * a);
    for (int c = 0; c < 4; c++)
      for (int a = 0; a < 3; a++) s.cons[h][3 + c] |= ent[h][18 + c * 3 + a] << (8 * a);
    for (int w = 0; w < 3; w++)
      for (int a = 0; a < 2; a++) s.cons[h][8 + w] |= ent[h][qIdx(w, a)] << (8 * a);
  }
  return s;
}
__constant__ Sched c_sched = makeSched();

__device__ unsigned int g_ticks;

__device__ __forceinline__ uint32_t smem_u32(const void* p) { return (uint32_t)__cvta_generic_to_shared(p); }
__device__ __forceinline__ void mbar_init(uint32_t bar, uint32_t cnt) {
  asm volatile("mbarrier.init.shared::cta.b64 [%0], %1;" ::"r"(bar), "r"(cnt) : "memory");
}
__device__ __forceinline__ void mbar_wait(uint32_t bar, uint32_t parity) {
  asm volatile(
      "{\n"
      ".reg .pred p;\n"
      ".reg .u32 n;\n"
      "mov.u32 n, 0;\n"
      "LAB_WAIT:\n"
      "mbarrier.try_wait.parity.shared::cta.b64 p, [%0], %1;\n"
      "@p bra LAB_DONE;\n"
      "add.u32 n, n, 1;\n"
      "setp.lt.u32 p, n, 0x80000;\n"
      "@p bra LAB_WAIT;\n"
      "trap;\n"
      "LAB_DONE:\n"
      "}\n" ::"r"(bar),
      "r"(parity)
      : "memory");
}
__device__ __forceinline__ bool mbar_test(uint32_t bar, uint32_t parity) {
  uint32_t ok;
  asm volatile("{\n.reg .pred p;\nmbarrier.test_wait.parity.shared::cta.b64 p, [%1], %2;\nselp.u32 %0, 1, 0, p;\n}\n"
               : "=r"(ok)
               : "r"(bar), "r"(parity)
               : "memory");
  return ok;
}
__device__ __forceinline__ void wait_full(uint32_t bars, uint32_t entry) { mbar_wait(bars + 8 * (entry & 15u), (entry >> 4) & 1u); }
__device__ __forceinline__ bool test_full(uint32_t bars, uint32_t entry) { return mbar_test(bars + 8 * (entry & 15u), (entry >> 4) & 1u); }
__device__ __forceinline__ uint32_t map_to_cta(uint32_t addr, uint32_t cta) {
  uint32_t r;
  asm("mapa.shared::cluster.u32 %0, %1, %2;" : "=r"(r) : "r"(addr), "r"(cta));
  return r;
}
__device__ __forceinline__ void release_slot(uint32_t bars, uint32_t entry, uint32_t lane, uint32_t count) {
  asm volatile(
      "{\n"
      ".reg .pred p;\n"
      "setp.lt.u32 p, %1, %3;\n"
      "@p mbarrier.arrive.shared::cluster.b64 _, [%0], %2;\n"
      "}\n" ::"r"(bars + 8 * (entry & 15u)),
      "r"(lane), "r"(count), "r"((entry >> 4) & 2u)
      : "memory");
}
__device__ __forceinline__ void tma_load(uint32_t dst, const CUtensorMap* m, uint32_t bar, int row, int cb, uint64_t pol) {
  asm volatile(
      "{\n.reg .pred p;\nelect.sync _|p, 0xffffffff;\n"
      "@p mbarrier.arrive.expect_tx.shared::cta.b64 _, [%2], 16384;\n"
      "@p cp.async.bulk.tensor.3d.shared::cluster.global.mbarrier::complete_tx::bytes.L2::cache_hint"
      " [%0], [%1, {%3, %4, %5}], [%2], %6;\n}\n" ::"r"(dst),
      "l"(m), "r"(bar), "r"(0), "r"(row), "r"(cb), "l"(pol)
      : "memory");
}
__device__ __forceinline__ void tma_load_mc(uint32_t dst, const CUtensorMap* m, uint32_t bar, int row, int cb, uint64_t pol) {
  asm volatile(
      "{\n.reg .pred p;\nelect.sync _|p, 0xffffffff;\n"
      "@p mbarrier.arrive.expect_tx.shared::cta.b64 _, [%2], 16384;\n"
      "@p cp.async.bulk.tensor.3d.shared::cluster.global.mbarrier::complete_tx::bytes.multicast::cluster.L2::cache_hint"
      " [%0], [%1, {%3, %4, %5}], [%2], %6, %7;\n}\n" ::"r"(dst),
      "l"(m), "r"(bar), "r"(0), "r"(row), "r"(cb), "h"((uint16_t)3), "l"(pol)
      : "memory");
}
__device__ __forceinline__ void prefetch_l2(const void* p) { asm volatile("prefetch.global.L2 [%0];" ::"l"(p) : "memory"); }
__device__ __forceinline__ void cluster_arrive() { asm volatile("barrier.cluster.arrive.relaxed.aligned;" ::: "memory"); }
__device__ __forceinline__ void cluster_wait() { asm volatile("barrier.cluster.wait.aligned;" ::: "memory"); }
__device__ __forceinline__ void turn_wait(int id) { asm volatile("bar.sync %0, 256;" ::"r"(id) : "memory"); }
__device__ __forceinline__ void turn_pass(int id) { asm volatile("bar.arrive %0, 256;" ::"r"(id) : "memory"); }
template <int N>
__device__ __forceinline__ void wg_wait() {
  asm volatile("wgmma.wait_group.sync.aligned %0;" ::"n"(N) : "memory");
}
__device__ __forceinline__ float ex2(float x) {
  float y;
  asm("ex2.approx.ftz.f32 %0, %1;" : "=f"(y) : "f"(x));
  return y;
}
__device__ __forceinline__ float rcp(float x) {
  float y;
  asm("rcp.approx.ftz.f32 %0, %1;" : "=f"(y) : "f"(x));
  return y;
}
__device__ __forceinline__ uint32_t pack_bf16(float lo, float hi) {
  uint32_t r;
  asm("cvt.rn.bf16x2.f32 %0, %1, %2;" : "=r"(r) : "f"(hi), "f"(lo));
  return r;
}
__device__ __forceinline__ void scale_bf16x2(uint32_t& x, uint32_t fh, uint32_t fl) {
  asm("{\n.reg .b32 t;\nmul.rn.bf16x2 t, %0, %2;\nfma.rn.bf16x2 %0, %0, %1, t;\n}\n" : "+r"(x) : "r"(fh), "r"(fl));
}

constexpr uint32_t kDescHi = 64u | (1u << 30);
__device__ __forceinline__ uint32_t desc_lo(uint32_t addr) { return ((addr & 0x3FFFF) >> 4) | (1u << 16); }

#define ACC8(a, o) \
  "+f"(a[o]), "+f"(a[o + 1]), "+f"(a[o + 2]), "+f"(a[o + 3]), "+f"(a[o + 4]), "+f"(a[o + 5]), "+f"(a[o + 6]), "+f"(a[o + 7])
#define IN8(a, o) \
  "r"(a[o]), "r"(a[o + 1]), "r"(a[o + 2]), "r"(a[o + 3]), "r"(a[o + 4]), "r"(a[o + 5]), "r"(a[o + 6]), "r"(a[o + 7])
#define REGS32 "{%0,%1,%2,%3,%4,%5,%6,%7,%8,%9,%10,%11,%12,%13,%14,%15,%16,%17,%18,%19,%20,%21,%22,%23,%24,%25,%26,%27,%28,%29,%30,%31}"
#define REGS64 "{%0,%1,%2,%3,%4,%5,%6,%7,%8,%9,%10,%11,%12,%13,%14,%15,%16,%17,%18,%19,%20,%21,%22,%23,%24,%25,%26,%27,%28,%29,%30,%31,%32,%33,%34,%35,%36,%37,%38,%39,%40,%41,%42,%43,%44,%45,%46,%47,%48,%49,%50,%51,%52,%53,%54,%55,%56,%57,%58,%59,%60,%61,%62,%63}"

__device__ __forceinline__ void mma_qk(float (&d)[64], uint32_t qa, uint32_t kb, int accumulate) {
  asm volatile(
      "{\n.reg .pred p;\n.reg .b32 a, b;\n.reg .b64 da, db;\n"
      "setp.ne.b32 p, %66, 0;\n"
      "wgmma.fence.sync.aligned;\n"
      "mov.b64 da, {%64, %67};\nmov.b64 db, {%65, %67};\n"
      "wgmma.mma_async.sync.aligned.m64n128k16.f32.bf16.bf16 " REGS64 ", da, db, p, 1, 1, 0, 0;\n"
      "add.u32 a, %64, 2;\nadd.u32 b, %65, 2;\nmov.b64 da, {a, %67};\nmov.b64 db, {b, %67};\n"
      "wgmma.mma_async.sync.aligned.m64n128k16.f32.bf16.bf16 " REGS64 ", da, db, 1, 1, 1, 0, 0;\n"
      "add.u32 a, %64, 4;\nadd.u32 b, %65, 4;\nmov.b64 da, {a, %67};\nmov.b64 db, {b, %67};\n"
      "wgmma.mma_async.sync.aligned.m64n128k16.f32.bf16.bf16 " REGS64 ", da, db, 1, 1, 1, 0, 0;\n"
      "add.u32 a, %64, 6;\nadd.u32 b, %65, 6;\nmov.b64 da, {a, %67};\nmov.b64 db, {b, %67};\n"
      "wgmma.mma_async.sync.aligned.m64n128k16.f32.bf16.bf16 " REGS64 ", da, db, 1, 1, 1, 0, 0;\n"
      "wgmma.commit_group.sync.aligned;\n}\n"
      : ACC8(d, 0), ACC8(d, 8), ACC8(d, 16), ACC8(d, 24), ACC8(d, 32), ACC8(d, 40), ACC8(d, 48), ACC8(d, 56)
      : "r"(qa), "r"(kb), "r"(accumulate), "n"(kDescHi)
      : "memory");
}
__device__ __forceinline__ void mma_pv(float (&d)[32], const uint32_t* a, uint32_t vb, int accumulate) {
  asm volatile(
      "{\n.reg .pred p;\n.reg .b32 b;\n.reg .b64 db;\n"
      "setp.ne.b32 p, %65, 0;\n"
      "wgmma.fence.sync.aligned;\n"
      "mov.b64 db, {%64, %66};\n"
      "wgmma.mma_async.sync.aligned.m64n64k16.f32.bf16.bf16 " REGS32 ", {%32,%33,%34,%35}, db, p, 1, 1, 1;\n"
      "add.u32 b, %64, 128;\nmov.b64 db, {b, %66};\n"
      "wgmma.mma_async.sync.aligned.m64n64k16.f32.bf16.bf16 " REGS32 ", {%36,%37,%38,%39}, db, 1, 1, 1, 1;\n"
      "add.u32 b, %64, 256;\nmov.b64 db, {b, %66};\n"
      "wgmma.mma_async.sync.aligned.m64n64k16.f32.bf16.bf16 " REGS32 ", {%40,%41,%42,%43}, db, 1, 1, 1, 1;\n"
      "add.u32 b, %64, 384;\nmov.b64 db, {b, %66};\n"
      "wgmma.mma_async.sync.aligned.m64n64k16.f32.bf16.bf16 " REGS32 ", {%44,%45,%46,%47}, db, 1, 1, 1, 1;\n"
      "add.u32 b, %64, 512;\nmov.b64 db, {b, %66};\n"
      "wgmma.mma_async.sync.aligned.m64n64k16.f32.bf16.bf16 " REGS32 ", {%48,%49,%50,%51}, db, 1, 1, 1, 1;\n"
      "add.u32 b, %64, 640;\nmov.b64 db, {b, %66};\n"
      "wgmma.mma_async.sync.aligned.m64n64k16.f32.bf16.bf16 " REGS32 ", {%52,%53,%54,%55}, db, 1, 1, 1, 1;\n"
      "add.u32 b, %64, 768;\nmov.b64 db, {b, %66};\n"
      "wgmma.mma_async.sync.aligned.m64n64k16.f32.bf16.bf16 " REGS32 ", {%56,%57,%58,%59}, db, 1, 1, 1, 1;\n"
      "add.u32 b, %64, 896;\nmov.b64 db, {b, %66};\n"
      "wgmma.mma_async.sync.aligned.m64n64k16.f32.bf16.bf16 " REGS32 ", {%60,%61,%62,%63}, db, 1, 1, 1, 1;\n"
      "wgmma.commit_group.sync.aligned;\n}\n"
      : ACC8(d, 0), ACC8(d, 8), ACC8(d, 16), ACC8(d, 24)
      : IN8(a, 0), IN8(a, 8), IN8(a, 16), IN8(a, 24), "r"(vb), "r"(accumulate), "n"(kDescHi)
      : "memory");
}
template <int N>
__device__ __forceinline__ void keep_regs(float (&d)[N]) {
#pragma unroll
  for (int i = 0; i < N; i++) asm volatile("" : "+f"(d[i])::"memory");
}

__device__ __forceinline__ uint4 quad_transpose(uint32_t a0, uint32_t a1, uint32_t a2, uint32_t a3, bool b0, bool b1) {
  uint32_t s0 = b0 ? a0 : a1, s1 = b0 ? a2 : a3;
  uint32_t r0 = __shfl_xor_sync(0xffffffffu, s0, 1), r1 = __shfl_xor_sync(0xffffffffu, s1, 1);
  uint32_t c0 = b0 ? r0 : a0, c1 = b0 ? a1 : r0, c2 = b0 ? r1 : a2, c3 = b0 ? a3 : r1;
  uint32_t t0 = b1 ? c0 : c2, t1 = b1 ? c1 : c3;
  uint32_t u0 = __shfl_xor_sync(0xffffffffu, t0, 2), u1 = __shfl_xor_sync(0xffffffffu, t1, 2);
  uint4 r;
  r.x = b1 ? u0 : c0;
  r.y = b1 ? u1 : c1;
  r.z = b1 ? c2 : u0;
  r.w = b1 ? c3 : u1;
  return r;
}

constexpr float kScaleLog2 = 0.0625f * 1.4426950408889634f;
constexpr float kRescaleThreshold = 8.f;

template <int N>
__device__ __forceinline__ void rescale_p(uint32_t* P, float f0, float f1) {
  const uint32_t h0 = pack_bf16(f0, f0), h1 = pack_bf16(f1, f1);
  const float r0 = f0 - __uint_as_float(h0 << 16), r1 = f1 - __uint_as_float(h1 << 16);
  const uint32_t l0 = pack_bf16(r0, r0), l1 = pack_bf16(r1, r1);
#pragma unroll
  for (int i = 0; i < N / 2; i++) {
    scale_bf16x2(P[2 * i], h0, l0);
    scale_bf16x2(P[2 * i + 1], h1, l1);
  }
}
__device__ __forceinline__ void row_max_float(const float (&s)[64], float& mx0, float& mx1) {
  mx0 = fmaxf(s[0], s[1]), mx1 = fmaxf(s[2], s[3]);
#pragma unroll
  for (int i = 1; i < 16; i++) {
    mx0 = fmaxf(mx0, fmaxf(s[4 * i], s[4 * i + 1]));
    mx1 = fmaxf(mx1, fmaxf(s[4 * i + 2], s[4 * i + 3]));
  }
  mx0 = fmaxf(mx0, __shfl_xor_sync(0xffffffffu, mx0, 1));
  mx1 = fmaxf(mx1, __shfl_xor_sync(0xffffffffu, mx1, 1));
  mx0 = fmaxf(mx0, __shfl_xor_sync(0xffffffffu, mx0, 2));
  mx1 = fmaxf(mx1, __shfl_xor_sync(0xffffffffu, mx1, 2));
}
__device__ __forceinline__ void row_max_int(const float (&s)[64], float& mx0, float& mx1) {
  int a0 = max(__float_as_int(s[0]), __float_as_int(s[1])), a1 = max(__float_as_int(s[2]), __float_as_int(s[3]));
  int b0 = max(__float_as_int(s[4]), __float_as_int(s[5])), b1 = max(__float_as_int(s[6]), __float_as_int(s[7]));
#pragma unroll
  for (int i = 1; i < 8; i++) {
    a0 = __vimax3_s32(a0, __float_as_int(s[8 * i]), __float_as_int(s[8 * i + 1]));
    a1 = __vimax3_s32(a1, __float_as_int(s[8 * i + 2]), __float_as_int(s[8 * i + 3]));
    b0 = __vimax3_s32(b0, __float_as_int(s[8 * i + 4]), __float_as_int(s[8 * i + 5]));
    b1 = __vimax3_s32(b1, __float_as_int(s[8 * i + 6]), __float_as_int(s[8 * i + 7]));
  }
  a0 = max(a0, b0);
  a1 = max(a1, b1);
  a0 = max(a0, __shfl_xor_sync(0xffffffffu, a0, 1));
  a1 = max(a1, __shfl_xor_sync(0xffffffffu, a1, 1));
  a0 = max(a0, __shfl_xor_sync(0xffffffffu, a0, 2));
  a1 = max(a1, __shfl_xor_sync(0xffffffffu, a1, 2));
  mx0 = __int_as_float(a0);
  mx1 = __int_as_float(a1);
}

template <int J>
__device__ __forceinline__ void softmax_chunk(float (&s)[64], uint32_t (&P)[96], float (&m)[2], float (&l)[2]) {
  float mx0, mx1;
  row_max_int(s, mx0, mx1);
  bool redo = (__float_as_int(mx0) | __float_as_int(mx1)) < 0;
  if (J > 0)
    redo = redo || fmaf(mx0, kScaleLog2, -m[0]) > kRescaleThreshold || fmaf(mx1, kScaleLog2, -m[1]) > kRescaleThreshold;
  if (__any_sync(0xffffffffu, redo)) {
    row_max_float(s, mx0, mx1);
    if (J > 0) {
      const float n0 = fmaxf(m[0], mx0 * kScaleLog2), n1 = fmaxf(m[1], mx1 * kScaleLog2);
      const float f0 = ex2(m[0] - n0), f1 = ex2(m[1] - n1);
      rescale_p<32 * J>(P, f0, f1);
      l[0] *= f0, l[1] *= f1;
      m[0] = n0, m[1] = n1;
    }
  }
  if (J == 0) m[0] = mx0 * kScaleLog2, m[1] = mx1 * kScaleLog2;
  float a0 = J ? l[0] : 0.f, a1 = J ? l[1] : 0.f, b0 = 0.f, b1 = 0.f;
#pragma unroll
  for (int ii = 0; ii < 16; ii++) {
    const int i = ii ^ 8;
    s[4 * i] = ex2(fmaf(s[4 * i], kScaleLog2, -m[0]));
    s[4 * i + 1] = ex2(fmaf(s[4 * i + 1], kScaleLog2, -m[0]));
    s[4 * i + 2] = ex2(fmaf(s[4 * i + 2], kScaleLog2, -m[1]));
    s[4 * i + 3] = ex2(fmaf(s[4 * i + 3], kScaleLog2, -m[1]));
    a0 += s[4 * i];
    b0 += s[4 * i + 1];
    a1 += s[4 * i + 2];
    b1 += s[4 * i + 3];
    P[32 * J + 2 * i] = pack_bf16(s[4 * i], s[4 * i + 1]);
    P[32 * J + 2 * i + 1] = pack_bf16(s[4 * i + 2], s[4 * i + 3]);
  }
  l[0] = a0 + b0;
  l[1] = a1 + b1;
}

__global__ void __cluster_dims__(2, 1, 1) __launch_bounds__(kThreads, 1)
    mha_kernel(const __grid_constant__ CUtensorMap mapQ, const __grid_constant__ CUtensorMap mapK,
               const __grid_constant__ CUtensorMap mapV, const char* __restrict__ gq, const char* __restrict__ gk,
               char* __restrict__ out, const int coresident) {
  extern __shared__ unsigned char smem_raw[];
  const uint32_t base = (smem_u32(smem_raw) + 1023u) & ~1023u;
  const uint32_t bar_full = base + kSlots * kSlotBytes;
  const uint32_t bar_empty = bar_full + 128;
  const int wg = __shfl_sync(0xffffffffu, (int)(threadIdx.x >> 7), 0);
  const int rank = blockIdx.x & 1;
  const int cid = blockIdx.x >> 1;

  if (wg == 3) {
    const uint32_t t_entry = clock();
    const uint32_t pace_word = bar_full + 256;
    if (threadIdx.x < 384 + kSlots) {
      mbar_init(bar_full + 8 * (threadIdx.x - 384), 1);
      mbar_init(bar_empty + 8 * (threadIdx.x - 384), kEmptyCount);
      asm volatile("fence.mbarrier_init.release.cluster;" ::: "memory");
    } else if (threadIdx.x >= 416 && threadIdx.x < 419) {
      asm volatile("prefetch.tensormap [%0];" ::"l"(threadIdx.x == 416 ? &mapQ : threadIdx.x == 417 ? &mapK : &mapV) : "memory");
    } else if (threadIdx.x == 448) {
      asm volatile("st.shared.v2.u32 [%0], {%1, %1};" ::"r"(pace_word), "r"(0) : "memory");
    }
    asm volatile("bar.sync 4, 128;" ::: "memory");
    cluster_arrive();
    asm volatile("setmaxnreg.dec.sync.aligned.u32 32;");
    const int pw = __shfl_sync(0xffffffffu, (int)(threadIdx.x >> 5) & 3, 0);
    if (pw >= 2) cluster_wait();

    if (pw == kIssuers) {
      if (rank == 0 && coresident) {
#pragma unroll 1
        for (int n = 0; n < (1 << 16); n++) {
          uint32_t seen, done;
          asm volatile("ld.relaxed.gpu.global.u32 %0, [%1];" : "=r"(seen) : "l"(&g_ticks) : "memory");
          asm volatile("st.volatile.shared.u32 [%0], %1;" ::"r"(pace_word), "r"(seen) : "memory");
          asm volatile("ld.volatile.shared.u32 %0, [%1];" : "=r"(done) : "r"(pace_word + 4) : "memory");
          if (done) break;
          __nanosleep(100);
        }
      }
    } else {
      const bool pacer = pw == 0 && rank == 0 && coresident;
      uint64_t pol_stream, pol_normal;
      asm volatile("createpolicy.fractional.L2::evict_first.b64 %0, 1.0;" : "=l"(pol_stream));
      asm volatile("createpolicy.fractional.L2::evict_normal.b64 %0, 1.0;" : "=l"(pol_normal));
      if (coresident) {
        const uint32_t delay = max(cid - kWarmClusters, 0) * kStaggerClocks;
        while ((uint32_t)clock() - t_entry < delay) __nanosleep(20);
      }
      int tick = 0;
#pragma unroll 1
      for (int i = pw; i < kLoads; i += kIssuers) {
        const uint32_t e = c_sched.prod[i];
        const uint32_t sl = e & 15u, kind = (e >> 5) & 3u;
        const uint32_t dst = base + sl * kSlotBytes, fb = bar_full + 8 * sl;
        const int row = (int)(e >> 12) * 64 + cid * kSeq, cb = (e >> 8) & 3u;
        mbar_wait(bar_empty + 8 * sl, ((e >> 4) & 1u) ^ 1u);
        if (pacer) {
          const int lead = kLeadEnd + kLeadExtra * min(max(kFadeEnd - tick, 0), kFadeEnd - kFadeBegin) / (kFadeEnd - kFadeBegin);
#pragma unroll 1
          for (int n = 0; n < 256; n++) {
            uint32_t seen;
            asm volatile("ld.volatile.shared.u32 %0, [%1];" : "=r"(seen) : "r"(pace_word) : "memory");
            if (tick * kClusters - (int)seen <= lead) break;
            __nanosleep(40);
          }
          tick++;
        }
        const uint64_t pol = i >= kStreamFrom ? pol_stream : pol_normal;
        if (kind == 0) tma_load(dst, &mapQ, fb, row + rank * 192, cb, pol);
        else tma_load_mc(dst + rank * 8192, kind == 1 ? &mapK : &mapV, fb, row + rank * 64, cb, pol);
        if (i < 2) cluster_wait();
        if (pacer && (threadIdx.x & 31) == 0)
          asm volatile("red.relaxed.gpu.global.inc.u32 [%0], %1;" ::"l"(&g_ticks), "r"(kTicks * kClusters - 1) : "memory");
      }
      if (pacer) asm volatile("st.volatile.shared.u32 [%0], %1;" ::"r"(pace_word + 4), "r"(1) : "memory");
    }
  } else {
    cluster_arrive();
    if (cid < kWarmClusters) {
      const size_t off = (size_t)cid * kHeadBytes + threadIdx.x * 128;
      prefetch_l2(gq + off + rank * 98304);
      prefetch_l2(gk + off + rank * 65536);
      prefetch_l2(gq + off + rank * 98304 + 49152);
      if (threadIdx.x < 128) prefetch_l2(gk + off + rank * 65536 + 49152);
    }
    asm volatile("setmaxnreg.inc.sync.aligned.u32 160;");
    const uint32_t lane = threadIdx.x & 31;
    const uint32_t dbase = desc_lo(base);
    const uint32_t rel_bar = map_to_cta(bar_empty, lane & 1);
    const int my_turn = 1 + wg, next_turn = 1 + (wg == 2 ? 0 : wg + 1);
    cluster_wait();
    if (wg == 2) turn_pass(1);
    const bool b0 = lane & 1, b1 = lane & 2;
    const uint32_t out_off =
        (uint32_t)(rank * 192 + wg * 64 + ((threadIdx.x >> 5) & 3) * 16 + (lane >> 2)) * 512u + (lane & 3) * 16u;

#pragma unroll 1
    for (int h = 0; h < kRounds; h++) {
      uint32_t P[96];
      float m[2], l[2];
      const uint32_t qw = c_sched.cons[h][8 + wg];

      auto qk_chunk = [&](auto jc) {
        constexpr int j = decltype(jc)::value;
        float s[64];
        const uint32_t kw = c_sched.cons[h][j];
        if (j == 0) wait_full(bar_full, qw);
        wait_full(bar_full, kw);
        turn_wait(my_turn);
#pragma unroll
        for (int cb = 0; cb < 4; cb++) {
          const uint32_t e = kw >> (8 * cb);
          bool ready = true;
          if (cb < 3) ready = test_full(bar_full, e >> 8);
          if (j == 0 && cb == 1) ready = ready && test_full(bar_full, qw >> 8);
          mma_qk(s, dbase + ((cb < 2 ? qw : qw >> 8) & 15u) * 1024 + (cb & 1) * 512, dbase + (e & 15u) * 1024, cb != 0);
          if (cb > 0) {
            wg_wait<1>();
            if (cb == 3) turn_pass(next_turn);
            release_slot(rel_bar, kw >> (8 * cb - 8), lane, 1);
            if (j == 2 && cb == 2) release_slot(rel_bar, qw, lane, 3);
          }
          if (!ready) {
            if (j == 0 && cb == 1) wait_full(bar_full, qw >> 8);
            wait_full(bar_full, e >> 8);
          }
        }
        wg_wait<0>();
        keep_regs(s);
        release_slot(rel_bar, kw >> 24, lane, 1);
        if (j == 2) release_slot(rel_bar, qw >> 8, lane, 3);
        softmax_chunk<j>(s, P, m, l);
      };
      qk_chunk(std::integral_constant<int, 0>{});
      qk_chunk(std::integral_constant<int, 1>{});
      qk_chunk(std::integral_constant<int, 2>{});
      l[0] += __shfl_xor_sync(0xffffffffu, l[0], 1);
      l[1] += __shfl_xor_sync(0xffffffffu, l[1], 1);
      l[0] += __shfl_xor_sync(0xffffffffu, l[0], 2);
      l[1] += __shfl_xor_sync(0xffffffffu, l[1], 2);
      const float inv0 = rcp(l[0]), inv1 = rcp(l[1]);

      char* optr = out + (size_t)(cid + h * kClusters) * kHeadBytes + out_off;
#pragma unroll 1
      for (int c = 0; c < 4; c++) {
        float o[32];
        const uint32_t vw = c_sched.cons[h][3 + c];
        wait_full(bar_full, vw);
        turn_wait(my_turn);
#pragma unroll
        for (int j = 0; j < 3; j++) {
          const uint32_t e = vw >> (8 * j);
          bool ready = true;
          if (j < 2) ready = test_full(bar_full, e >> 8);
          mma_pv(o, P + 32 * j, dbase + (e & 15u) * 1024, j != 0);
          if (j > 0) {
            wg_wait<1>();
            if (j == 2 && !(wg == 2 && c == 3 && h == kRounds - 1)) turn_pass(next_turn);
            release_slot(rel_bar, vw >> (8 * j - 8), lane, 1);
          }
          if (!ready) wait_full(bar_full, e >> 8);
        }
        wg_wait<0>();
        keep_regs(o);
        release_slot(rel_bar, vw >> 16, lane, 1);
#pragma unroll
        for (int q = 0; q < 2; q++) {
#pragma unroll
          for (int r = 0; r < 2; r++) {
            const int b = 16 * q + 2 * r;
            const float f = r ? inv1 : inv0;
            *reinterpret_cast<uint4*>(optr + r * 4096 + q * 64) =
                quad_transpose(pack_bf16(o[b] * f, o[b + 1] * f), pack_bf16(o[b + 4] * f, o[b + 5] * f),
                               pack_bf16(o[b + 8] * f, o[b + 9] * f), pack_bf16(o[b + 12] * f, o[b + 13] * f), b0, b1);
          }
        }
        optr += 128;
      }
    }
  }
}

typedef CUresult (*EncodeTiledFn)(CUtensorMap*, CUtensorMapDataType, cuuint32_t, void*, const cuuint64_t*,
                                  const cuuint64_t*, const cuuint32_t*, const cuuint32_t*, CUtensorMapInterleave,
                                  CUtensorMapSwizzle, CUtensorMapL2promotion, CUtensorMapFloatOOBfill);

CUtensorMap make_map(EncodeTiledFn enc, const void* ptr, uint32_t boxBlocks) {
  CUtensorMap m;
  cuuint64_t dims[3] = {64, (cuuint64_t)kHeads * kSeq, 4};
  cuuint64_t strides[2] = {512, 128};
  cuuint32_t box[3] = {64, 64, boxBlocks};
  cuuint32_t es[3] = {1, 1, 1};
  enc(&m, CU_TENSOR_MAP_DATA_TYPE_BFLOAT16, 3, const_cast<void*>(ptr), dims, strides, box, es,
      CU_TENSOR_MAP_INTERLEAVE_NONE, CU_TENSOR_MAP_SWIZZLE_128B, CU_TENSOR_MAP_L2_PROMOTION_L2_128B,
      CU_TENSOR_MAP_FLOAT_OOB_FILL_NONE);
  return m;
}

}

extern "C" void kernel_launch(void* const* d_in, const int* in_sizes, int n_in, void* d_out, int out_size) {
  static EncodeTiledFn enc = nullptr;
  static int coresident = 0;
  if (!enc) {
    void* fn = nullptr;
    cudaDriverEntryPointQueryResult qr;
    cudaGetDriverEntryPoint("cuTensorMapEncodeTiled", &fn, cudaEnableDefault, &qr);
    enc = (EncodeTiledFn)fn;
    cudaFuncSetAttribute(mha_kernel, cudaFuncAttributeMaxDynamicSharedMemorySize, kSmemBytes);
    int dev = 0, sms = 0;
    cudaGetDevice(&dev);
    cudaDeviceGetAttribute(&sms, cudaDevAttrMultiProcessorCount, dev);
    coresident = sms >= 2 * kClusters + 4;
  }
  const CUtensorMap mq = make_map(enc, d_in[0], 2);
  const CUtensorMap mk = make_map(enc, d_in[1], 1);
  const CUtensorMap mv = make_map(enc, d_in[2], 1);
  mha_kernel<<<2 * kClusters, kThreads, kSmemBytes, cudaStreamPerThread>>>(
      mq, mk, mv, (const char*)d_in[0], (const char*)d_in[1], (char*)d_out, coresident);
}
```

```cpp
#include <cuda_runtime.h>
#include <cuda_bf16.h>
#include <cuda.h>
#include <stdint.h>
#include <type_traits>

namespace {

constexpr int kSeq = 384;
constexpr int kHeads = 512;
constexpr int kHeadBytes = kSeq * 512;
constexpr int kClusters = 64;
constexpr int kRounds = kHeads / kClusters;
constexpr int kSlots = 14;
constexpr int kSlotBytes = 16384;
constexpr int kUnits = 30;
constexpr int kLoads = kRounds * kUnits;
constexpr int kThreads = 512;
constexpr int kSmemBytes = kSlots * kSlotBytes + 1024   + 1024  ;
constexpr uint32_t kEmptyCount = 24;

constexpr int kIssuers = 3;
constexpr int kWarmClusters = 8;
constexpr int kStaggerClocks = 225;
constexpr int kStreamFrom = 190;
constexpr int kPrefBegin = 14, kPrefEnd = 22;
constexpr int kPrefAhead = 4;
constexpr int kPrefUntil = 150;
constexpr int kTicks = kLoads / kIssuers;
constexpr int kLeadEnd = 105;
constexpr int kLeadExtra = 130;
constexpr int kFadeBegin = 40, kFadeEnd = 70;

constexpr int kIdx(int u) { return u < 4 ? 2 + u : 6 + u; }
constexpr int qIdx(int w, int h) { return w == 0 ? h : 4 + 2 * w + h; }
struct Sched {
  uint32_t cons[kRounds][12];
  uint32_t prod[kLoads];
};
constexpr Sched makeSched() {
  Sched s{};
  int rel[kUnits] = {};
  int n = 0;
  for (int g = 0; g < 3; g++)
    for (int w = 0; w < 3; w++)
      for (int a = 0; a < 4; a++) {
        if (w == 2) rel[n++] = kIdx(g * 4 + a);
        if (g == 2 && (a & 1)) rel[n++] = qIdx(w, a / 2);
      }
  for (int x = 0; x < 12; x++) rel[n++] = 18 + x;
  const int last_v[12] = {4, 5, 6, 8, 9, 10, 12, 13, 15, 18, 19, 20};
  int slot[kLoads] = {};
  uint32_t ent[kRounds][kUnits] = {};
  int uses[kSlots] = {};
  for (int i = 0; i < kLoads; i++) {
    const int h = i / kUnits, u = i % kUnits;
    int sl = i;
    if (i >= kSlots) {
      const int k = (h == kRounds - 1 && u >= 18) ? h * kUnits + last_v[u - 18] : i - kSlots;
      const int prev = (k / kUnits) * kUnits + rel[k % kUnits];
      sl = slot[prev];
      ent[prev / kUnits][prev % kUnits] |= 32u;
    }
    slot[i] = sl;
    ent[h][u] = (uint32_t)(sl | ((uses[sl]++ & 1) << 4));
    int kind = 0, cb = 0, r64 = 0;
    if (u < 2 || (u >= 6 && u < 10)) {
      cb = (u & 1) * 2, r64 = u < 2 ? 0 : (u - 4) / 2;
    } else if (u < 18) {
      const int ku = u < 6 ? u - 2 : u - 6;
      kind = 1, cb = ku & 3, r64 = (ku / 4) * 2;
    } else {
      kind = 2, cb = (u - 18) / 3, r64 = ((u - 18) % 3) * 2;
    }
    const int pref = u >= kPrefBegin && u < kPrefEnd && i < kPrefUntil;
    s.prod[i] = ent[h][u] | (uint32_t)(kind << 5) | (uint32_t)(pref << 7) | (uint32_t)(cb << 8) |
                (uint32_t)((h * kClusters * 6 + r64) << 12);
  }
  for (int h = 0; h < kRounds; h++) {
    for (int g = 0; g < 3; g++)
      for (int a = 0; a < 4; a++) s.cons[h][g] |= ent[h][kIdx(g * 4 + a)] << (8 * a);
    for (int c = 0; c < 4; c++)
      for (int a = 0; a < 3; a++) s.cons[h][3 + c] |= ent[h][18 + c * 3 + a] << (8 * a);
    for (int w = 0; w < 3; w++)
      for (int a = 0; a < 2; a++) s.cons[h][8 + w] |= ent[h][qIdx(w, a)] << (8 * a);
  }
  return s;
}
static_assert(kPrefBegin + kPrefAhead >= 18 && kPrefEnd - 1 + kPrefAhead < kUnits, "prefetch targets must be V tiles");
__constant__ Sched c_sched = makeSched();

__device__ unsigned int g_ticks;

__device__ __forceinline__ uint32_t smem_u32(const void* p) { return (uint32_t)__cvta_generic_to_shared(p); }
__device__ __forceinline__ void mbar_init(uint32_t bar, uint32_t cnt) {
  asm volatile("mbarrier.init.shared::cta.b64 [%0], %1;" ::"r"(bar), "r"(cnt) : "memory");
}
__device__ __forceinline__ void mbar_wait(uint32_t bar, uint32_t parity) {
  asm volatile(
      "{\n"
      ".reg .pred p;\n"
      ".reg .u32 n;\n"
      "mov.u32 n, 0;\n"
      "LAB_WAIT:\n"
      "mbarrier.try_wait.parity.shared::cta.b64 p, [%0], %1;\n"
      "@p bra LAB_DONE;\n"
      "add.u32 n, n, 1;\n"
      "setp.lt.u32 p, n, 0x80000;\n"
      "@p bra LAB_WAIT;\n"
      "trap;\n"
      "LAB_DONE:\n"
      "}\n" ::"r"(bar),
      "r"(parity)
      : "memory");
}
__device__ __forceinline__ bool mbar_test(uint32_t bar, uint32_t parity) {
  uint32_t ok;
  asm volatile("{\n.reg .pred p;\nmbarrier.test_wait.parity.shared::cta.b64 p, [%1], %2;\nselp.u32 %0, 1, 0, p;\n}\n"
               : "=r"(ok)
               : "r"(bar), "r"(parity)
               : "memory");
  return ok;
}
__device__ __forceinline__ void wait_full(uint32_t bars, uint32_t entry) { mbar_wait(bars + 8 * (entry & 15u), (entry >> 4) & 1u); }
__device__ __forceinline__ bool test_full(uint32_t bars, uint32_t entry) { return mbar_test(bars + 8 * (entry & 15u), (entry >> 4) & 1u); }
__device__ __forceinline__ uint32_t map_to_cta(uint32_t addr, uint32_t cta) {
  uint32_t r;
  asm("mapa.shared::cluster.u32 %0, %1, %2;" : "=r"(r) : "r"(addr), "r"(cta));
  return r;
}
__device__ __forceinline__ void release_slot(uint32_t bars, uint32_t entry, uint32_t lane, uint32_t count) {
  asm volatile(
      "{\n"
      ".reg .pred p;\n"
      "setp.lt.u32 p, %1, %3;\n"
      "@p mbarrier.arrive.shared::cluster.b64 _, [%0], %2;\n"
      "}\n" ::"r"(bars + 8 * (entry & 15u)),
      "r"(lane), "r"(count), "r"((entry >> 4) & 2u)
      : "memory");
}
__device__ __forceinline__ void tma_load(uint32_t dst, const CUtensorMap* m, uint32_t bar, int row, int cb, uint64_t pol) {
  asm volatile(
      "{\n.reg .pred p;\nelect.sync _|p, 0xffffffff;\n"
      "@p mbarrier.arrive.expect_tx.shared::cta.b64 _, [%2], 16384;\n"
      "@p cp.async.bulk.tensor.3d.shared::cluster.global.mbarrier::complete_tx::bytes.L2::cache_hint"
      " [%0], [%1, {%3, %4, %5}], [%2], %6;\n}\n" ::"r"(dst),
      "l"(m), "r"(bar), "r"(0), "r"(row), "r"(cb), "l"(pol)
      : "memory");
}
__device__ __forceinline__ void tma_load_mc(uint32_t dst, const CUtensorMap* m, uint32_t bar, int row, int cb, uint64_t pol) {
  asm volatile(
      "{\n.reg .pred p;\nelect.sync _|p, 0xffffffff;\n"
      "@p mbarrier.arrive.expect_tx.shared::cta.b64 _, [%2], 16384;\n"
      "@p cp.async.bulk.tensor.3d.shared::cluster.global.mbarrier::complete_tx::bytes.multicast::cluster.L2::cache_hint"
      " [%0], [%1, {%3, %4, %5}], [%2], %6, %7;\n}\n" ::"r"(dst),
      "l"(m), "r"(bar), "r"(0), "r"(row), "r"(cb), "h"((uint16_t)3), "l"(pol)
      : "memory");
}
__device__ __forceinline__ void tma_prefetch(const CUtensorMap* m, int row, int cb, uint64_t pol) {
  asm volatile(
      "{\n.reg .pred p;\nelect.sync _|p, 0xffffffff;\n"
      "@p cp.async.bulk.prefetch.tensor.3d.L2.global.L2::cache_hint [%0, {%1, %2, %3}], %4;\n}\n" ::"l"(m),
      "r"(0), "r"(row), "r"(cb), "l"(pol)
      : "memory");
}
__device__ __forceinline__ void prefetch_l2(const void* p) { asm volatile("prefetch.global.L2 [%0];" ::"l"(p) : "memory"); }
__device__ __forceinline__ void cluster_arrive() { asm volatile("barrier.cluster.arrive.relaxed.aligned;" ::: "memory"); }
__device__ __forceinline__ void cluster_wait() { asm volatile("barrier.cluster.wait.aligned;" ::: "memory"); }
__device__ __forceinline__ void turn_wait(int id) { asm volatile("bar.sync %0, 256;" ::"r"(id) : "memory"); }
__device__ __forceinline__ void turn_pass(int id) { asm volatile("bar.arrive %0, 256;" ::"r"(id) : "memory"); }
template <int N>
__device__ __forceinline__ void wg_wait() {
  asm volatile("wgmma.wait_group.sync.aligned %0;" ::"n"(N) : "memory");
}
__device__ __forceinline__ float ex2(float x) {
  float y;
  asm("ex2.approx.ftz.f32 %0, %1;" : "=f"(y) : "f"(x));
  return y;
}
__device__ __forceinline__ float rcp(float x) {
  float y;
  asm("rcp.approx.ftz.f32 %0, %1;" : "=f"(y) : "f"(x));
  return y;
}
__device__ __forceinline__ uint32_t pack_bf16(float lo, float hi) {
  uint32_t r;
  asm("cvt.rn.bf16x2.f32 %0, %1, %2;" : "=r"(r) : "f"(hi), "f"(lo));
  return r;
}
__device__ __forceinline__ void scale_bf16x2(uint32_t& x, uint32_t fh, uint32_t fl) {
  asm("{\n.reg .b32 t;\nmul.rn.bf16x2 t, %0, %2;\nfma.rn.bf16x2 %0, %0, %1, t;\n}\n" : "+r"(x) : "r"(fh), "r"(fl));
}

constexpr uint32_t kDescHi = 64u | (1u << 30);
__device__ __forceinline__ uint32_t desc_lo(uint32_t addr) { return ((addr & 0x3FFFF) >> 4) | (1u << 16); }

#define ACC8(a, o) \
  "+f"(a[o]), "+f"(a[o + 1]), "+f"(a[o + 2]), "+f"(a[o + 3]), "+f"(a[o + 4]), "+f"(a[o + 5]), "+f"(a[o + 6]), "+f"(a[o + 7])
#define IN8(a, o) \
  "r"(a[o]), "r"(a[o + 1]), "r"(a[o + 2]), "r"(a[o + 3]), "r"(a[o + 4]), "r"(a[o + 5]), "r"(a[o + 6]), "r"(a[o + 7])
#define REGS32 "{%0,%1,%2,%3,%4,%5,%6,%7,%8,%9,%10,%11,%12,%13,%14,%15,%16,%17,%18,%19,%20,%21,%22,%23,%24,%25,%26,%27,%28,%29,%30,%31}"
#define REGS64 "{%0,%1,%2,%3,%4,%5,%6,%7,%8,%9,%10,%11,%12,%13,%14,%15,%16,%17,%18,%19,%20,%21,%22,%23,%24,%25,%26,%27,%28,%29,%30,%31,%32,%33,%34,%35,%36,%37,%38,%39,%40,%41,%42,%43,%44,%45,%46,%47,%48,%49,%50,%51,%52,%53,%54,%55,%56,%57,%58,%59,%60,%61,%62,%63}"

__device__ __forceinline__ void mma_qk(float (&d)[64], uint32_t qa, uint32_t kb, int accumulate) {
  asm volatile(
      "{\n.reg .pred p;\n.reg .b32 a, b;\n.reg .b64 da, db;\n"
      "setp.ne.b32 p, %66, 0;\n"
      "wgmma.fence.sync.aligned;\n"
      "mov.b64 da, {%64, %67};\nmov.b64 db, {%65, %67};\n"
      "wgmma.mma_async.sync.aligned.m64n128k16.f32.bf16.bf16 " REGS64 ", da, db, p, 1, 1, 0, 0;\n"
      "add.u32 a, %64, 2;\nadd.u32 b, %65, 2;\nmov.b64 da, {a, %67};\nmov.b64 db, {b, %67};\n"
      "wgmma.mma_async.sync.aligned.m64n128k16.f32.bf16.bf16 " REGS64 ", da, db, 1, 1, 1, 0, 0;\n"
      "add.u32 a, %64, 4;\nadd.u32 b, %65, 4;\nmov.b64 da, {a, %67};\nmov.b64 db, {b, %67};\n"
      "wgmma.mma_async.sync.aligned.m64n128k16.f32.bf16.bf16 " REGS64 ", da, db, 1, 1, 1, 0, 0;\n"
      "add.u32 a, %64, 6;\nadd.u32 b, %65, 6;\nmov.b64 da, {a, %67};\nmov.b64 db, {b, %67};\n"
      "wgmma.mma_async.sync.aligned.m64n128k16.f32.bf16.bf16 " REGS64 ", da, db, 1, 1, 1, 0, 0;\n"
      "wgmma.commit_group.sync.aligned;\n}\n"
      : ACC8(d, 0), ACC8(d, 8), ACC8(d, 16), ACC8(d, 24), ACC8(d, 32), ACC8(d, 40), ACC8(d, 48), ACC8(d, 56)
      : "r"(qa), "r"(kb), "r"(accumulate), "n"(kDescHi)
      : "memory");
}
__device__ __forceinline__ void mma_pv(float (&d)[32], const uint32_t* a, uint32_t vb, int accumulate) {
  asm volatile(
      "{\n.reg .pred p;\n.reg .b32 b;\n.reg .b64 db;\n"
      "setp.ne.b32 p, %65, 0;\n"
      "wgmma.fence.sync.aligned;\n"
      "mov.b64 db, {%64, %66};\n"
      "wgmma.mma_async.sync.aligned.m64n64k16.f32.bf16.bf16 " REGS32 ", {%32,%33,%34,%35}, db, p, 1, 1, 1;\n"
      "add.u32 b, %64, 128;\nmov.b64 db, {b, %66};\n"
      "wgmma.mma_async.sync.aligned.m64n64k16.f32.bf16.bf16 " REGS32 ", {%36,%37,%38,%39}, db, 1, 1, 1, 1;\n"
      "add.u32 b, %64, 256;\nmov.b64 db, {b, %66};\n"
      "wgmma.mma_async.sync.aligned.m64n64k16.f32.bf16.bf16 " REGS32 ", {%40,%41,%42,%43}, db, 1, 1, 1, 1;\n"
      "add.u32 b, %64, 384;\nmov.b64 db, {b, %66};\n"
      "wgmma.mma_async.sync.aligned.m64n64k16.f32.bf16.bf16 " REGS32 ", {%44,%45,%46,%47}, db, 1, 1, 1, 1;\n"
      "add.u32 b, %64, 512;\nmov.b64 db, {b, %66};\n"
      "wgmma.mma_async.sync.aligned.m64n64k16.f32.bf16.bf16 " REGS32 ", {%48,%49,%50,%51}, db, 1, 1, 1, 1;\n"
      "add.u32 b, %64, 640;\nmov.b64 db, {b, %66};\n"
      "wgmma.mma_async.sync.aligned.m64n64k16.f32.bf16.bf16 " REGS32 ", {%52,%53,%54,%55}, db, 1, 1, 1, 1;\n"
      "add.u32 b, %64, 768;\nmov.b64 db, {b, %66};\n"
      "wgmma.mma_async.sync.aligned.m64n64k16.f32.bf16.bf16 " REGS32 ", {%56,%57,%58,%59}, db, 1, 1, 1, 1;\n"
      "add.u32 b, %64, 896;\nmov.b64 db, {b, %66};\n"
      "wgmma.mma_async.sync.aligned.m64n64k16.f32.bf16.bf16 " REGS32 ", {%60,%61,%62,%63}, db, 1, 1, 1, 1;\n"
      "wgmma.commit_group.sync.aligned;\n}\n"
      : ACC8(d, 0), ACC8(d, 8), ACC8(d, 16), ACC8(d, 24)
      : IN8(a, 0), IN8(a, 8), IN8(a, 16), IN8(a, 24), "r"(vb), "r"(accumulate), "n"(kDescHi)
      : "memory");
}
template <int N>
__device__ __forceinline__ void keep_regs(float (&d)[N]) {
#pragma unroll
  for (int i = 0; i < N; i++) asm volatile("" : "+f"(d[i])::"memory");
}

__device__ __forceinline__ uint4 quad_transpose(uint32_t a0, uint32_t a1, uint32_t a2, uint32_t a3, bool b0, bool b1) {
  uint32_t s0 = b0 ? a0 : a1, s1 = b0 ? a2 : a3;
  uint32_t r0 = __shfl_xor_sync(0xffffffffu, s0, 1), r1 = __shfl_xor_sync(0xffffffffu, s1, 1);
  uint32_t c0 = b0 ? r0 : a0, c1 = b0 ? a1 : r0, c2 = b0 ? r1 : a2, c3 = b0 ? a3 : r1;
  uint32_t t0 = b1 ? c0 : c2, t1 = b1 ? c1 : c3;
  uint32_t u0 = __shfl_xor_sync(0xffffffffu, t0, 2), u1 = __shfl_xor_sync(0xffffffffu, t1, 2);
  uint4 r;
  r.x = b1 ? u0 : c0;
  r.y = b1 ? u1 : c1;
  r.z = b1 ? c2 : u0;
  r.w = b1 ? c3 : u1;
  return r;
}

constexpr float kScaleLog2 = 0.0625f * 1.4426950408889634f;
constexpr float kRescaleThreshold = 8.f;

template <int N>
__device__ __forceinline__ void rescale_p(uint32_t* P, float f0, float f1) {
  const uint32_t h0 = pack_bf16(f0, f0), h1 = pack_bf16(f1, f1);
  const float r0 = f0 - __uint_as_float(h0 << 16), r1 = f1 - __uint_as_float(h1 << 16);
  const uint32_t l0 = pack_bf16(r0, r0), l1 = pack_bf16(r1, r1);
#pragma unroll
  for (int i = 0; i < N / 2; i++) {
    scale_bf16x2(P[2 * i], h0, l0);
    scale_bf16x2(P[2 * i + 1], h1, l1);
  }
}
__device__ __forceinline__ void row_max_float(const float (&s)[64], float& mx0, float& mx1) {
  mx0 = fmaxf(s[0], s[1]), mx1 = fmaxf(s[2], s[3]);
#pragma unroll
  for (int i = 1; i < 16; i++) {
    mx0 = fmaxf(mx0, fmaxf(s[4 * i], s[4 * i + 1]));
    mx1 = fmaxf(mx1, fmaxf(s[4 * i + 2], s[4 * i + 3]));
  }
  mx0 = fmaxf(mx0, __shfl_xor_sync(0xffffffffu, mx0, 1));
  mx1 = fmaxf(mx1, __shfl_xor_sync(0xffffffffu, mx1, 1));
  mx0 = fmaxf(mx0, __shfl_xor_sync(0xffffffffu, mx0, 2));
  mx1 = fmaxf(mx1, __shfl_xor_sync(0xffffffffu, mx1, 2));
}
__device__ __forceinline__ void row_max_int(const float (&s)[64], float& mx0, float& mx1) {
  int a0 = max(__float_as_int(s[0]), __float_as_int(s[1])), a1 = max(__float_as_int(s[2]), __float_as_int(s[3]));
  int b0 = max(__float_as_int(s[4]), __float_as_int(s[5])), b1 = max(__float_as_int(s[6]), __float_as_int(s[7]));
#pragma unroll
  for (int i = 1; i < 8; i++) {
    a0 = __vimax3_s32(a0, __float_as_int(s[8 * i]), __float_as_int(s[8 * i + 1]));
    a1 = __vimax3_s32(a1, __float_as_int(s[8 * i + 2]), __float_as_int(s[8 * i + 3]));
    b0 = __vimax3_s32(b0, __float_as_int(s[8 * i + 4]), __float_as_int(s[8 * i + 5]));
    b1 = __vimax3_s32(b1, __float_as_int(s[8 * i + 6]), __float_as_int(s[8 * i + 7]));
  }
  a0 = max(a0, b0);
  a1 = max(a1, b1);
  a0 = max(a0, __shfl_xor_sync(0xffffffffu, a0, 1));
  a1 = max(a1, __shfl_xor_sync(0xffffffffu, a1, 1));
  a0 = max(a0, __shfl_xor_sync(0xffffffffu, a0, 2));
  a1 = max(a1, __shfl_xor_sync(0xffffffffu, a1, 2));
  mx0 = __int_as_float(a0);
  mx1 = __int_as_float(a1);
}

template <int J>
__device__ __forceinline__ void softmax_chunk(float (&s)[64], uint32_t (&P)[96], float (&m)[2], float (&l)[2]) {
  float mx0, mx1;
  row_max_int(s, mx0, mx1);
  bool redo = (__float_as_int(mx0) | __float_as_int(mx1)) < 0;
  if (J > 0)
    redo = redo || fmaf(mx0, kScaleLog2, -m[0]) > kRescaleThreshold || fmaf(mx1, kScaleLog2, -m[1]) > kRescaleThreshold;
  if (__any_sync(0xffffffffu, redo)) {
    row_max_float(s, mx0, mx1);
    if (J > 0) {
      const float n0 = fmaxf(m[0], mx0 * kScaleLog2), n1 = fmaxf(m[1], mx1 * kScaleLog2);
      const float f0 = ex2(m[0] - n0), f1 = ex2(m[1] - n1);
      rescale_p<32 * J>(P, f0, f1);
      l[0] *= f0, l[1] *= f1;
      m[0] = n0, m[1] = n1;
    }
  }
  if (J == 0) m[0] = mx0 * kScaleLog2, m[1] = mx1 * kScaleLog2;
  float a0 = J ? l[0] : 0.f, a1 = J ? l[1] : 0.f, b0 = 0.f, b1 = 0.f;
#pragma unroll
  for (int ii = 0; ii < 16; ii++) {
    const int i = ii ^ 8;
    s[4 * i] = ex2(fmaf(s[4 * i], kScaleLog2, -m[0]));
    s[4 * i + 1] = ex2(fmaf(s[4 * i + 1], kScaleLog2, -m[0]));
    s[4 * i + 2] = ex2(fmaf(s[4 * i + 2], kScaleLog2, -m[1]));
    s[4 * i + 3] = ex2(fmaf(s[4 * i + 3], kScaleLog2, -m[1]));
    a0 += s[4 * i];
    b0 += s[4 * i + 1];
    a1 += s[4 * i + 2];
    b1 += s[4 * i + 3];
    P[32 * J + 2 * i] = pack_bf16(s[4 * i], s[4 * i + 1]);
    P[32 * J + 2 * i + 1] = pack_bf16(s[4 * i + 2], s[4 * i + 3]);
  }
  l[0] = a0 + b0;
  l[1] = a1 + b1;
}

__global__ void __cluster_dims__(2, 1, 1) __launch_bounds__(kThreads, 1)
    mha_kernel(const __grid_constant__ CUtensorMap mapQ, const __grid_constant__ CUtensorMap mapK,
               const __grid_constant__ CUtensorMap mapV, const char* __restrict__ gq, const char* __restrict__ gk,
               char* __restrict__ out, const int coresident) {
  extern __shared__ unsigned char smem_raw[];
  const uint32_t base = (smem_u32(smem_raw) + 1023u) & ~1023u;
  const uint32_t bar_full = base + kSlots * kSlotBytes;
  const uint32_t bar_empty = bar_full + 128;
  const int wg = __shfl_sync(0xffffffffu, (int)(threadIdx.x >> 7), 0);
  const int rank = blockIdx.x & 1;
  const int cid = blockIdx.x >> 1;

  if (wg == 3) {
    const uint32_t t_entry = clock();
    const uint32_t pace_word = bar_full + 256;
    if (threadIdx.x < 384 + kSlots) {
      mbar_init(bar_full + 8 * (threadIdx.x - 384), 1);
      mbar_init(bar_empty + 8 * (threadIdx.x - 384), kEmptyCount);
      asm volatile("fence.mbarrier_init.release.cluster;" ::: "memory");
    } else if (threadIdx.x >= 416 && threadIdx.x < 419) {
      asm volatile("prefetch.tensormap [%0];" ::"l"(threadIdx.x == 416 ? &mapQ : threadIdx.x == 417 ? &mapK : &mapV) : "memory");
    } else if (threadIdx.x == 448) {
      asm volatile("st.shared.v2.u32 [%0], {%1, %1};" ::"r"(pace_word), "r"(0) : "memory");
    }
    asm volatile("bar.sync 4, 128;" ::: "memory");
    cluster_arrive();
    asm volatile("setmaxnreg.dec.sync.aligned.u32 32;");
    const int pw = __shfl_sync(0xffffffffu, (int)(threadIdx.x >> 5) & 3, 0);
    if (pw >= 2) cluster_wait();

    if (pw == kIssuers) {
      if (rank == 0 && coresident) {
#pragma unroll 1
        for (int n = 0; n < (1 << 16); n++) {
          uint32_t seen, done;
          asm volatile("ld.relaxed.gpu.global.u32 %0, [%1];" : "=r"(seen) : "l"(&g_ticks) : "memory");
          asm volatile("st.volatile.shared.u32 [%0], %1;" ::"r"(pace_word), "r"(seen) : "memory");
          asm volatile("ld.volatile.shared.u32 %0, [%1];" : "=r"(done) : "r"(pace_word + 4) : "memory");
          if (done) break;
          __nanosleep(100);
        }
      }
    } else {
      const bool pacer = pw == 0 && rank == 0 && coresident;
      uint64_t pol_stream, pol_normal;
      asm volatile("createpolicy.fractional.L2::evict_first.b64 %0, 1.0;" : "=l"(pol_stream));
      asm volatile("createpolicy.fractional.L2::evict_normal.b64 %0, 1.0;" : "=l"(pol_normal));
      if (coresident) {
        const uint32_t delay = max(cid - kWarmClusters, 0) * kStaggerClocks;
        while ((uint32_t)clock() - t_entry < delay) __nanosleep(20);
      }
      int tick = 0;
#pragma unroll 1
      for (int i = pw; i < kLoads; i += kIssuers) {
        const uint32_t e = c_sched.prod[i];
        const uint32_t sl = e & 15u, kind = (e >> 5) & 3u;
        const uint32_t dst = base + sl * kSlotBytes, fb = bar_full + 8 * sl;
        const int row = (int)(e >> 12) * 64 + cid * kSeq, cb = (e >> 8) & 3u;
        mbar_wait(bar_empty + 8 * sl, ((e >> 4) & 1u) ^ 1u);
        if (pacer) {
          const int lead = kLeadEnd + kLeadExtra * min(max(kFadeEnd - tick, 0), kFadeEnd - kFadeBegin) / (kFadeEnd - kFadeBegin);
#pragma unroll 1
          for (int n = 0; n < 256; n++) {
            uint32_t seen;
            asm volatile("ld.volatile.shared.u32 %0, [%1];" : "=r"(seen) : "r"(pace_word) : "memory");
            if (tick * kClusters - (int)seen <= lead) break;
            __nanosleep(40);
          }
          tick++;
        }
        const uint64_t pol = i >= kStreamFrom ? pol_stream : pol_normal;
        if (kind == 0) tma_load(dst, &mapQ, fb, row + rank * 192, cb, pol);
        else tma_load_mc(dst + rank * 8192, kind == 1 ? &mapK : &mapV, fb, row + rank * 64, cb, pol);
        if (e & 128u) {
          const uint32_t en = c_sched.prod[i + kPrefAhead];
          tma_prefetch(&mapV, (int)(en >> 12) * 64 + cid * kSeq + rank * 64, (en >> 8) & 3u, pol_normal);
        }
        if (i < 2) cluster_wait();
        if (pacer && (threadIdx.x & 31) == 0)
          asm volatile("red.relaxed.gpu.global.inc.u32 [%0], %1;" ::"l"(&g_ticks), "r"(kTicks * kClusters - 1) : "memory");
      }
      if (pacer) asm volatile("st.volatile.shared.u32 [%0], %1;" ::"r"(pace_word + 4), "r"(1) : "memory");
    }
  } else {
    cluster_arrive();
    if (cid < kWarmClusters) {
      const size_t off = (size_t)cid * kHeadBytes + threadIdx.x * 128;
      prefetch_l2(gq + off + rank * 98304);
      prefetch_l2(gk + off + rank * 65536);
      prefetch_l2(gq + off + rank * 98304 + 49152);
      if (threadIdx.x < 128) prefetch_l2(gk + off + rank * 65536 + 49152);
    }
    asm volatile("setmaxnreg.inc.sync.aligned.u32 160;");
    const uint32_t lane = threadIdx.x & 31;
    const uint32_t dbase = desc_lo(base);
    const uint32_t rel_bar = map_to_cta(bar_empty, lane & 1);
    const int my_turn = 1 + wg, next_turn = 1 + (wg == 2 ? 0 : wg + 1);
    cluster_wait();
    if (wg == 2) turn_pass(1);
    const bool b0 = lane & 1, b1 = lane & 2;
    const uint32_t out_off =
        (uint32_t)(rank * 192 + wg * 64 + ((threadIdx.x >> 5) & 3) * 16 + (lane >> 2)) * 512u + (lane & 3) * 16u;

#pragma unroll 1
    for (int h = 0; h < kRounds; h++) {
      uint32_t P[96];
      float m[2], l[2];
      const uint32_t qw = c_sched.cons[h][8 + wg];

      auto qk_chunk = [&](auto jc) {
        constexpr int j = decltype(jc)::value;
        float s[64];
        const uint32_t kw = c_sched.cons[h][j];
        if (j == 0) wait_full(bar_full, qw);
        wait_full(bar_full, kw);
        turn_wait(my_turn);
#pragma unroll
        for (int cb = 0; cb < 4; cb++) {
          const uint32_t e = kw >> (8 * cb);
          bool ready = true;
          if (cb < 3) ready = test_full(bar_full, e >> 8);
          if (j == 0 && cb == 1) ready = ready && test_full(bar_full, qw >> 8);
          mma_qk(s, dbase + ((cb < 2 ? qw : qw >> 8) & 15u) * 1024 + (cb & 1) * 512, dbase + (e & 15u) * 1024, cb != 0);
          if (cb > 0) {
            wg_wait<1>();
            if (cb == 3) turn_pass(next_turn);
            release_slot(rel_bar, kw >> (8 * cb - 8), lane, 1);
            if (j == 2 && cb == 2) release_slot(rel_bar, qw, lane, 3);
          }
          if (!ready) {
            if (j == 0 && cb == 1) wait_full(bar_full, qw >> 8);
            wait_full(bar_full, e >> 8);
          }
        }
        wg_wait<0>();
        keep_regs(s);
        release_slot(rel_bar, kw >> 24, lane, 1);
        if (j == 2) release_slot(rel_bar, qw >> 8, lane, 3);
        softmax_chunk<j>(s, P, m, l);
      };
      qk_chunk(std::integral_constant<int, 0>{});
      qk_chunk(std::integral_constant<int, 1>{});
      qk_chunk(std::integral_constant<int, 2>{});
      l[0] += __shfl_xor_sync(0xffffffffu, l[0], 1);
      l[1] += __shfl_xor_sync(0xffffffffu, l[1], 1);
      l[0] += __shfl_xor_sync(0xffffffffu, l[0], 2);
      l[1] += __shfl_xor_sync(0xffffffffu, l[1], 2);
      const float inv0 = rcp(l[0]), inv1 = rcp(l[1]);

      char* optr = out + (size_t)(cid + h * kClusters) * kHeadBytes + out_off;
#pragma unroll 1
      for (int c = 0; c < 4; c++) {
        float o[32];
        const uint32_t vw = c_sched.cons[h][3 + c];
        wait_full(bar_full, vw);
        turn_wait(my_turn);
#pragma unroll
        for (int j = 0; j < 3; j++) {
          const uint32_t e = vw >> (8 * j);
          bool ready = true;
          if (j < 2) ready = test_full(bar_full, e >> 8);
          mma_pv(o, P + 32 * j, dbase + (e & 15u) * 1024, j != 0);
          if (j > 0) {
            wg_wait<1>();
            if (j == 2 && !(wg == 2 && c == 3 && h == kRounds - 1)) turn_pass(next_turn);
            release_slot(rel_bar, vw >> (8 * j - 8), lane, 1);
          }
          if (!ready) wait_full(bar_full, e >> 8);
        }
        wg_wait<0>();
        keep_regs(o);
        release_slot(rel_bar, vw >> 16, lane, 1);
#pragma unroll
        for (int q = 0; q < 2; q++) {
#pragma unroll
          for (int r = 0; r < 2; r++) {
            const int b = 16 * q + 2 * r;
            const float f = r ? inv1 : inv0;
            *reinterpret_cast<uint4*>(optr + r * 4096 + q * 64) =
                quad_transpose(pack_bf16(o[b] * f, o[b + 1] * f), pack_bf16(o[b + 4] * f, o[b + 5] * f),
                               pack_bf16(o[b + 8] * f, o[b + 9] * f), pack_bf16(o[b + 12] * f, o[b + 13] * f), b0, b1);
          }
        }
        optr += 128;
      }
    }
  }
}

typedef CUresult (*EncodeTiledFn)(CUtensorMap*, CUtensorMapDataType, cuuint32_t, void*, const cuuint64_t*,
                                  const cuuint64_t*, const cuuint32_t*, const cuuint32_t*, CUtensorMapInterleave,
                                  CUtensorMapSwizzle, CUtensorMapL2promotion, CUtensorMapFloatOOBfill);

CUtensorMap make_map(EncodeTiledFn enc, const void* ptr, uint32_t boxBlocks) {
  CUtensorMap m;
  cuuint64_t dims[3] = {64, (cuuint64_t)kHeads * kSeq, 4};
  cuuint64_t strides[2] = {512, 128};
  cuuint32_t box[3] = {64, 64, boxBlocks};
  cuuint32_t es[3] = {1, 1, 1};
  enc(&m, CU_TENSOR_MAP_DATA_TYPE_BFLOAT16, 3, const_cast<void*>(ptr), dims, strides, box, es,
      CU_TENSOR_MAP_INTERLEAVE_NONE, CU_TENSOR_MAP_SWIZZLE_128B, CU_TENSOR_MAP_L2_PROMOTION_L2_128B,
      CU_TENSOR_MAP_FLOAT_OOB_FILL_NONE);
  return m;
}

}

extern "C" void kernel_launch(void* const* d_in, const int* in_sizes, int n_in, void* d_out, int out_size) {
  static EncodeTiledFn enc = nullptr;
  static int coresident = 0;
  if (!enc) {
    void* fn = nullptr;
    cudaDriverEntryPointQueryResult qr;
    cudaGetDriverEntryPoint("cuTensorMapEncodeTiled", &fn, cudaEnableDefault, &qr);
    enc = (EncodeTiledFn)fn;
    cudaFuncSetAttribute(mha_kernel, cudaFuncAttributeMaxDynamicSharedMemorySize, kSmemBytes);
    int dev = 0, sms = 0;
    cudaGetDevice(&dev);
    cudaDeviceGetAttribute(&sms, cudaDevAttrMultiProcessorCount, dev);
    coresident = sms >= 2 * kClusters + 4;
  }
  const CUtensorMap mq = make_map(enc, d_in[0], 2);
  const CUtensorMap mk = make_map(enc, d_in[1], 1);
  const CUtensorMap mv = make_map(enc, d_in[2], 1);
  mha_kernel<<<2 * kClusters, kThreads, kSmemBytes, cudaStreamPerThread>>>(
      mq, mk, mv, (const char*)d_in[0], (const char*)d_in[1], (char*)d_out, coresident);
}
```

```cpp
#include <cuda_runtime.h>
#include <cuda_bf16.h>
#include <cuda.h>
#include <stdint.h>
#include <type_traits>

namespace {

constexpr int kSeq = 384;
constexpr int kHeads = 512;
constexpr int kHeadBytes = kSeq * 512;
constexpr int kClusters = 64;
constexpr int kRounds = kHeads / kClusters;
constexpr int kSlots = 14;
constexpr int kSlotBytes = 16384;
constexpr int kUnits = 30;
constexpr int kLoads = kRounds * kUnits;
constexpr int kThreads = 512;
constexpr int kSmemBytes = kSlots * kSlotBytes + 1024   + 1024  ;
constexpr uint32_t kEmptyCount = 24;

constexpr int kIssuers = 3;
constexpr int kWarmClusters = 8;
constexpr int kStaggerClocks = 225;
constexpr int kStreamFrom = 190;
constexpr int kPrefBegin = 14, kPrefEnd = 22;
constexpr int kPrefAhead = 4;
constexpr int kPrefUntil = 150;
constexpr int kTicks = kLoads / kIssuers;
constexpr int kLeadEnd = 105;
constexpr int kLeadExtra = 130;
constexpr int kFadeBegin = 40, kFadeEnd = 70;

constexpr int kIdx(int u) { return u < 4 ? 2 + u : 6 + u; }
constexpr int qIdx(int w, int h) { return w == 0 ? h : 4 + 2 * w + h; }
struct Sched {
  uint32_t cons[kRounds][12];
  uint32_t prod[kLoads];
};
constexpr Sched makeSched() {
  Sched s{};
  int rel[kUnits] = {};
  int n = 0;
  for (int g = 0; g < 3; g++)
    for (int w = 0; w < 3; w++)
      for (int a = 0; a < 4; a++) {
        if (w == 2) rel[n++] = kIdx(g * 4 + a);
        if (g == 2 && (a & 1)) rel[n++] = qIdx(w, a / 2);
      }
  for (int x = 0; x < 12; x++) rel[n++] = 18 + x;
  const int last_v[12] = {4, 5, 6, 8, 9, 10, 12, 13, 15, 18, 19, 20};
  int slot[kLoads] = {};
  uint32_t ent[kRounds][kUnits] = {};
  int uses[kSlots] = {};
  for (int i = 0; i < kLoads; i++) {
    const int h = i / kUnits, u = i % kUnits;
    int sl = i;
    if (i >= kSlots) {
      const int k = (h == kRounds - 1 && u >= 18) ? h * kUnits + last_v[u - 18] : i - kSlots;
      const int prev = (k / kUnits) * kUnits + rel[k % kUnits];
      sl = slot[prev];
      ent[prev / kUnits][prev % kUnits] |= 32u;
    }
    slot[i] = sl;
    ent[h][u] = (uint32_t)(sl | ((uses[sl]++ & 1) << 4));
    int kind = 0, cb = 0, r64 = 0;
    if (u < 2 || (u >= 6 && u < 10)) {
      cb = (u & 1) * 2, r64 = u < 2 ? 0 : (u - 4) / 2;
    } else if (u < 18) {
      const int ku = u < 6 ? u - 2 : u - 6;
      kind = 1, cb = ku & 3, r64 = (ku / 4) * 2;
    } else {
      kind = 2, cb = (u - 18) / 3, r64 = ((u - 18) % 3) * 2;
    }
    const int pref = u >= kPrefBegin && u < kPrefEnd && i < kPrefUntil;
    s.prod[i] = ent[h][u] | (uint32_t)(kind << 5) | (uint32_t)(pref << 7) | (uint32_t)(cb << 8) |
                (uint32_t)((h * kClusters * 6 + r64) << 12);
  }
  for (int h = 0; h < kRounds; h++) {
    for (int g = 0; g < 3; g++)
      for (int a = 0; a < 4; a++) s.cons[h][g] |= ent[h][kIdx(g * 4 + a)] << (8 * a);
    for (int c = 0; c < 4; c++)
      for (int a = 0; a < 3; a++) s.cons[h][3 + c] |= ent[h][18 + c * 3 + a] << (8 * a);
    for (int w = 0; w < 3; w++)
      for (int a = 0; a < 2; a++) s.cons[h][8 + w] |= ent[h][qIdx(w, a)] << (8 * a);
  }
  return s;
}
static_assert(kPrefBegin + kPrefAhead >= 18 && kPrefEnd - 1 + kPrefAhead < kUnits, "prefetch targets must be V tiles");
__constant__ Sched c_sched = makeSched();

__device__ unsigned int g_ticks;

__device__ __forceinline__ uint32_t smem_u32(const void* p) { return (uint32_t)__cvta_generic_to_shared(p); }
__device__ __forceinline__ void mbar_init(uint32_t bar, uint32_t cnt) {
  asm volatile("mbarrier.init.shared::cta.b64 [%0], %1;" ::"r"(bar), "r"(cnt) : "memory");
}
__device__ __forceinline__ void mbar_wait(uint32_t bar, uint32_t parity) {
  asm volatile(
      "{\n"
      ".reg .pred p;\n"
      ".reg .u32 n;\n"
      "mov.u32 n, 0;\n"
      "LAB_WAIT:\n"
      "mbarrier.try_wait.parity.shared::cta.b64 p, [%0], %1;\n"
      "@p bra LAB_DONE;\n"
      "add.u32 n, n, 1;\n"
      "setp.lt.u32 p, n, 0x80000;\n"
      "@p bra LAB_WAIT;\n"
      "trap;\n"
      "LAB_DONE:\n"
      "}\n" ::"r"(bar),
      "r"(parity)
      : "memory");
}
__device__ __forceinline__ bool mbar_test(uint32_t bar, uint32_t parity) {
  uint32_t ok;
  asm volatile("{\n.reg .pred p;\nmbarrier.test_wait.parity.shared::cta.b64 p, [%1], %2;\nselp.u32 %0, 1, 0, p;\n}\n"
               : "=r"(ok)
               : "r"(bar), "r"(parity)
               : "memory");
  return ok;
}
__device__ __forceinline__ void wait_full(uint32_t bars, uint32_t entry) { mbar_wait(bars + 8 * (entry & 15u), (entry >> 4) & 1u); }
__device__ __forceinline__ bool test_full(uint32_t bars, uint32_t entry) { return mbar_test(bars + 8 * (entry & 15u), (entry >> 4) & 1u); }
__device__ __forceinline__ uint32_t map_to_cta(uint32_t addr, uint32_t cta) {
  uint32_t r;
  asm("mapa.shared::cluster.u32 %0, %1, %2;" : "=r"(r) : "r"(addr), "r"(cta));
  return r;
}
__device__ __forceinline__ void release_slot(uint32_t bars, uint32_t entry, uint32_t lane, uint32_t count) {
  asm volatile(
      "{\n"
      ".reg .pred p;\n"
      "setp.lt.u32 p, %1, %3;\n"
      "@p mbarrier.arrive.shared::cluster.b64 _, [%0], %2;\n"
      "}\n" ::"r"(bars + 8 * (entry & 15u)),
      "r"(lane), "r"(count), "r"((entry >> 4) & 2u)
      : "memory");
}
__device__ __forceinline__ void tma_load(uint32_t dst, const CUtensorMap* m, uint32_t bar, int row, int cb, uint64_t pol) {
  asm volatile(
      "{\n.reg .pred p;\nelect.sync _|p, 0xffffffff;\n"
      "@p mbarrier.arrive.expect_tx.shared::cta.b64 _, [%2], 16384;\n"
      "@p cp.async.bulk.tensor.3d.shared::cluster.global.mbarrier::complete_tx::bytes.L2::cache_hint"
      " [%0], [%1, {%3, %4, %5}], [%2], %6;\n}\n" ::"r"(dst),
      "l"(m), "r"(bar), "r"(0), "r"(row), "r"(cb), "l"(pol)
      : "memory");
}
__device__ __forceinline__ void tma_load_mc(uint32_t dst, const CUtensorMap* m, uint32_t bar, int row, int cb, uint64_t pol) {
  asm volatile(
      "{\n.reg .pred p;\nelect.sync _|p, 0xffffffff;\n"
      "@p mbarrier.arrive.expect_tx.shared::cta.b64 _, [%2], 16384;\n"
      "@p cp.async.bulk.tensor.3d.shared::cluster.global.mbarrier::complete_tx::bytes.multicast::cluster.L2::cache_hint"
      " [%0], [%1, {%3, %4, %5}], [%2], %6, %7;\n}\n" ::"r"(dst),
      "l"(m), "r"(bar), "r"(0), "r"(row), "r"(cb), "h"((uint16_t)3), "l"(pol)
      : "memory");
}
__device__ __forceinline__ void tma_prefetch(const CUtensorMap* m, int row, int cb, uint64_t pol) {
  asm volatile(
      "{\n.reg .pred p;\nelect.sync _|p, 0xffffffff;\n"
      "@p cp.async.bulk.prefetch.tensor.3d.L2.global.L2::cache_hint [%0, {%1, %2, %3}], %4;\n}\n" ::"l"(m),
      "r"(0), "r"(row), "r"(cb), "l"(pol)
      : "memory");
}
__device__ __forceinline__ void prefetch_l2(const void* p) { asm volatile("prefetch.global.L2 [%0];" ::"l"(p) : "memory"); }
__device__ __forceinline__ void cluster_arrive() { asm volatile("barrier.cluster.arrive.relaxed.aligned;" ::: "memory"); }
__device__ __forceinline__ void cluster_wait() { asm volatile("barrier.cluster.wait.aligned;" ::: "memory"); }
__device__ __forceinline__ void turn_wait(int id) { asm volatile("bar.sync %0, 256;" ::"r"(id) : "memory"); }
__device__ __forceinline__ void turn_pass(int id) { asm volatile("bar.arrive %0, 256;" ::"r"(id) : "memory"); }
template <int N>
__device__ __forceinline__ void wg_wait() {
  asm volatile("wgmma.wait_group.sync.aligned %0;" ::"n"(N) : "memory");
}
__device__ __forceinline__ float ex2(float x) {
  float y;
  asm("ex2.approx.ftz.f32 %0, %1;" : "=f"(y) : "f"(x));
  return y;
}
__device__ __forceinline__ float rcp(float x) {
  float y;
  asm("rcp.approx.ftz.f32 %0, %1;" : "=f"(y) : "f"(x));
  return y;
}
__device__ __forceinline__ uint32_t pack_bf16(float lo, float hi) {
  uint32_t r;
  asm("cvt.rn.bf16x2.f32 %0, %1, %2;" : "=r"(r) : "f"(hi), "f"(lo));
  return r;
}
__device__ __forceinline__ void scale_bf16x2(uint32_t& x, uint32_t fh, uint32_t fl) {
  asm("{\n.reg .b32 t;\nmul.rn.bf16x2 t, %0, %2;\nfma.rn.bf16x2 %0, %0, %1, t;\n}\n" : "+r"(x) : "r"(fh), "r"(fl));
}

constexpr uint32_t kDescHi = 64u | (1u << 30);
__device__ __forceinline__ uint32_t desc_lo(uint32_t addr) { return ((addr & 0x3FFFF) >> 4) | (1u << 16); }

#define ACC8(a, o) \
  "+f"(a[o]), "+f"(a[o + 1]), "+f"(a[o + 2]), "+f"(a[o + 3]), "+f"(a[o + 4]), "+f"(a[o + 5]), "+f"(a[o + 6]), "+f"(a[o + 7])
#define IN8(a, o) \
  "r"(a[o]), "r"(a[o + 1]), "r"(a[o + 2]), "r"(a[o + 3]), "r"(a[o + 4]), "r"(a[o + 5]), "r"(a[o + 6]), "r"(a[o + 7])
#define REGS32 "{%0,%1,%2,%3,%4,%5,%6,%7,%8,%9,%10,%11,%12,%13,%14,%15,%16,%17,%18,%19,%20,%21,%22,%23,%24,%25,%26,%27,%28,%29,%30,%31}"
#define REGS64 "{%0,%1,%2,%3,%4,%5,%6,%7,%8,%9,%10,%11,%12,%13,%14,%15,%16,%17,%18,%19,%20,%21,%22,%23,%24,%25,%26,%27,%28,%29,%30,%31,%32,%33,%34,%35,%36,%37,%38,%39,%40,%41,%42,%43,%44,%45,%46,%47,%48,%49,%50,%51,%52,%53,%54,%55,%56,%57,%58,%59,%60,%61,%62,%63}"

__device__ __forceinline__ void mma_qk(float (&d)[64], uint32_t qa, uint32_t kb, int accumulate) {
  asm volatile(
      "{\n.reg .pred p;\n.reg .b32 a, b;\n.reg .b64 da, db;\n"
      "setp.ne.b32 p, %66, 0;\n"
      "wgmma.fence.sync.aligned;\n"
      "mov.b64 da, {%64, %67};\nmov.b64 db, {%65, %67};\n"
      "wgmma.mma_async.sync.aligned.m64n128k16.f32.bf16.bf16 " REGS64 ", da, db, p, 1, 1, 0, 0;\n"
      "add.u32 a, %64, 2;\nadd.u32 b, %65, 2;\nmov.b64 da, {a, %67};\nmov.b64 db, {b, %67};\n"
      "wgmma.mma_async.sync.aligned.m64n128k16.f32.bf16.bf16 " REGS64 ", da, db, 1, 1, 1, 0, 0;\n"
      "add.u32 a, %64, 4;\nadd.u32 b, %65, 4;\nmov.b64 da, {a, %67};\nmov.b64 db, {b, %67};\n"
      "wgmma.mma_async.sync.aligned.m64n128k16.f32.bf16.bf16 " REGS64 ", da, db, 1, 1, 1, 0, 0;\n"
      "add.u32 a, %64, 6;\nadd.u32 b, %65, 6;\nmov.b64 da, {a, %67};\nmov.b64 db, {b, %67};\n"
      "wgmma.mma_async.sync.aligned.m64n128k16.f32.bf16.bf16 " REGS64 ", da, db, 1, 1, 1, 0, 0;\n"
      "wgmma.commit_group.sync.aligned;\n}\n"
      : ACC8(d, 0), ACC8(d, 8), ACC8(d, 16), ACC8(d, 24), ACC8(d, 32), ACC8(d, 40), ACC8(d, 48), ACC8(d, 56)
      : "r"(qa), "r"(kb), "r"(accumulate), "n"(kDescHi)
      : "memory");
}
__device__ __forceinline__ void mma_pv(float (&d)[32], const uint32_t* a, uint32_t vb, int accumulate) {
  asm volatile(
      "{\n.reg .pred p;\n.reg .b32 b;\n.reg .b64 db;\n"
      "setp.ne.b32 p, %65, 0;\n"
      "wgmma.fence.sync.aligned;\n"
      "mov.b64 db, {%64, %66};\n"
      "wgmma.mma_async.sync.aligned.m64n64k16.f32.bf16.bf16 " REGS32 ", {%32,%33,%34,%35}, db, p, 1, 1, 1;\n"
      "add.u32 b, %64, 128;\nmov.b64 db, {b, %66};\n"
      "wgmma.mma_async.sync.aligned.m64n64k16.f32.bf16.bf16 " REGS32 ", {%36,%37,%38,%39}, db, 1, 1, 1, 1;\n"
      "add.u32 b, %64, 256;\nmov.b64 db, {b, %66};\n"
      "wgmma.mma_async.sync.aligned.m64n64k16.f32.bf16.bf16 " REGS32 ", {%40,%41,%42,%43}, db, 1, 1, 1, 1;\n"
      "add.u32 b, %64, 384;\nmov.b64 db, {b, %66};\n"
      "wgmma.mma_async.sync.aligned.m64n64k16.f32.bf16.bf16 " REGS32 ", {%44,%45,%46,%47}, db, 1, 1, 1, 1;\n"
      "add.u32 b, %64, 512;\nmov.b64 db, {b, %66};\n"
      "wgmma.mma_async.sync.aligned.m64n64k16.f32.bf16.bf16 " REGS32 ", {%48,%49,%50,%51}, db, 1, 1, 1, 1;\n"
      "add.u32 b, %64, 640;\nmov.b64 db, {b, %66};\n"
      "wgmma.mma_async.sync.aligned.m64n64k16.f32.bf16.bf16 " REGS32 ", {%52,%53,%54,%55}, db, 1, 1, 1, 1;\n"
      "add.u32 b, %64, 768;\nmov.b64 db, {b, %66};\n"
      "wgmma.mma_async.sync.aligned.m64n64k16.f32.bf16.bf16 " REGS32 ", {%56,%57,%58,%59}, db, 1, 1, 1, 1;\n"
      "add.u32 b, %64, 896;\nmov.b64 db, {b, %66};\n"
      "wgmma.mma_async.sync.aligned.m64n64k16.f32.bf16.bf16 " REGS32 ", {%60,%61,%62,%63}, db, 1, 1, 1, 1;\n"
      "wgmma.commit_group.sync.aligned;\n}\n"
      : ACC8(d, 0), ACC8(d, 8), ACC8(d, 16), ACC8(d, 24)
      : IN8(a, 0), IN8(a, 8), IN8(a, 16), IN8(a, 24), "r"(vb), "r"(accumulate), "n"(kDescHi)
      : "memory");
}
template <int N>
__device__ __forceinline__ void keep_regs(float (&d)[N]) {
#pragma unroll
  for (int i = 0; i < N; i++) asm volatile("" : "+f"(d[i])::"memory");
}

__device__ __forceinline__ uint4 quad_transpose(uint32_t a0, uint32_t a1, uint32_t a2, uint32_t a3, bool b0, bool b1) {
  uint32_t s0 = b0 ? a0 : a1, s1 = b0 ? a2 : a3;
  uint32_t r0 = __shfl_xor_sync(0xffffffffu, s0, 1), r1 = __shfl_xor_sync(0xffffffffu, s1, 1);
  uint32_t c0 = b0 ? r0 : a0, c1 = b0 ? a1 : r0, c2 = b0 ? r1 : a2, c3 = b0 ? a3 : r1;
  uint32_t t0 = b1 ? c0 : c2, t1 = b1 ? c1 : c3;
  uint32_t u0 = __shfl_xor_sync(0xffffffffu, t0, 2), u1 = __shfl_xor_sync(0xffffffffu, t1, 2);
  uint4 r;
  r.x = b1 ? u0 : c0;
  r.y = b1 ? u1 : c1;
  r.z = b1 ? c2 : u0;
  r.w = b1 ? c3 : u1;
  return r;
}

constexpr float kScaleLog2 = 0.0625f * 1.4426950408889634f;
constexpr float kRescaleThreshold = 8.f;

template <int N>
__device__ __forceinline__ void rescale_p(uint32_t* P, float f0, float f1) {
  const uint32_t h0 = pack_bf16(f0, f0), h1 = pack_bf16(f1, f1);
  const float r0 = f0 - __uint_as_float(h0 << 16), r1 = f1 - __uint_as_float(h1 << 16);
  const uint32_t l0 = pack_bf16(r0, r0), l1 = pack_bf16(r1, r1);
#pragma unroll
  for (int i = 0; i < N / 2; i++) {
    scale_bf16x2(P[2 * i], h0, l0);
    scale_bf16x2(P[2 * i + 1], h1, l1);
  }
}
__device__ __forceinline__ void row_max_float(const float (&s)[64], float& mx0, float& mx1) {
  mx0 = fmaxf(s[0], s[1]), mx1 = fmaxf(s[2], s[3]);
#pragma unroll
  for (int i = 1; i < 16; i++) {
    mx0 = fmaxf(mx0, fmaxf(s[4 * i], s[4 * i + 1]));
    mx1 = fmaxf(mx1, fmaxf(s[4 * i + 2], s[4 * i + 3]));
  }
  mx0 = fmaxf(mx0, __shfl_xor_sync(0xffffffffu, mx0, 1));
  mx1 = fmaxf(mx1, __shfl_xor_sync(0xffffffffu, mx1, 1));
  mx0 = fmaxf(mx0, __shfl_xor_sync(0xffffffffu, mx0, 2));
  mx1 = fmaxf(mx1, __shfl_xor_sync(0xffffffffu, mx1, 2));
}
__device__ __forceinline__ void row_max_int(const float (&s)[64], float& mx0, float& mx1) {
  int a0 = max(__float_as_int(s[0]), __float_as_int(s[1])), a1 = max(__float_as_int(s[2]), __float_as_int(s[3]));
  int b0 = max(__float_as_int(s[4]), __float_as_int(s[5])), b1 = max(__float_as_int(s[6]), __float_as_int(s[7]));
#pragma unroll
  for (int i = 1; i < 8; i++) {
    a0 = __vimax3_s32(a0, __float_as_int(s[8 * i]), __float_as_int(s[8 * i + 1]));
    a1 = __vimax3_s32(a1, __float_as_int(s[8 * i + 2]), __float_as_int(s[8 * i + 3]));
    b0 = __vimax3_s32(b0, __float_as_int(s[8 * i + 4]), __float_as_int(s[8 * i + 5]));
    b1 = __vimax3_s32(b1, __float_as_int(s[8 * i + 6]), __float_as_int(s[8 * i + 7]));
  }
  a0 = max(a0, b0);
  a1 = max(a1, b1);
  a0 = max(a0, __shfl_xor_sync(0xffffffffu, a0, 1));
  a1 = max(a1, __shfl_xor_sync(0xffffffffu, a1, 1));
  a0 = max(a0, __shfl_xor_sync(0xffffffffu, a0, 2));
  a1 = max(a1, __shfl_xor_sync(0xffffffffu, a1, 2));
  mx0 = __int_as_float(a0);
  mx1 = __int_as_float(a1);
}

template <int J>
__device__ __forceinline__ void softmax_chunk(float (&s)[64], uint32_t (&P)[96], float (&m)[2], float (&l)[2]) {
  float mx0, mx1;
  row_max_int(s, mx0, mx1);
  bool redo = (__float_as_int(mx0) | __float_as_int(mx1)) < 0;
  if (J > 0)
    redo = redo || fmaf(mx0, kScaleLog2, -m[0]) > kRescaleThreshold || fmaf(mx1, kScaleLog2, -m[1]) > kRescaleThreshold;
  if (__any_sync(0xffffffffu, redo)) {
    row_max_float(s, mx0, mx1);
    if (J > 0) {
      const float n0 = fmaxf(m[0], mx0 * kScaleLog2), n1 = fmaxf(m[1], mx1 * kScaleLog2);
      const float f0 = ex2(m[0] - n0), f1 = ex2(m[1] - n1);
      rescale_p<32 * J>(P, f0, f1);
      l[0] *= f0, l[1] *= f1;
      m[0] = n0, m[1] = n1;
    }
  }
  if (J == 0) m[0] = mx0 * kScaleLog2, m[1] = mx1 * kScaleLog2;
  float a0 = J ? l[0] : 0.f, a1 = J ? l[1] : 0.f, b0 = 0.f, b1 = 0.f;
#pragma unroll
  for (int ii = 0; ii < 16; ii++) {
    const int i = ii ^ 8;
    s[4 * i] = ex2(fmaf(s[4 * i], kScaleLog2, -m[0]));
    s[4 * i + 1] = ex2(fmaf(s[4 * i + 1], kScaleLog2, -m[0]));
    s[4 * i + 2] = ex2(fmaf(s[4 * i + 2], kScaleLog2, -m[1]));
    s[4 * i + 3] = ex2(fmaf(s[4 * i + 3], kScaleLog2, -m[1]));
    a0 += s[4 * i];
    b0 += s[4 * i + 1];
    a1 += s[4 * i + 2];
    b1 += s[4 * i + 3];
    P[32 * J + 2 * i] = pack_bf16(s[4 * i], s[4 * i + 1]);
    P[32 * J + 2 * i + 1] = pack_bf16(s[4 * i + 2], s[4 * i + 3]);
  }
  l[0] = a0 + b0;
  l[1] = a1 + b1;
}

__global__ void __cluster_dims__(2, 1, 1) __launch_bounds__(kThreads, 1)
    mha_kernel(const __grid_constant__ CUtensorMap mapQ, const __grid_constant__ CUtensorMap mapK,
               const __grid_constant__ CUtensorMap mapV, const char* __restrict__ gq, const char* __restrict__ gk,
               char* __restrict__ out, const int coresident) {
  extern __shared__ unsigned char smem_raw[];
  const uint32_t base = (smem_u32(smem_raw) + 1023u) & ~1023u;
  const uint32_t bar_full = base + kSlots * kSlotBytes;
  const uint32_t bar_empty = bar_full + 128;
  const int wg = __shfl_sync(0xffffffffu, (int)(threadIdx.x >> 7), 0);
  const int rank = blockIdx.x & 1;
  const int cid = blockIdx.x >> 1;

  if (wg == 3) {
    const uint32_t t_entry = clock();
    const uint32_t pace_word = bar_full + 256;
    if (threadIdx.x < 384 + kSlots) {
      mbar_init(bar_full + 8 * (threadIdx.x - 384), 1);
      mbar_init(bar_empty + 8 * (threadIdx.x - 384), kEmptyCount);
      asm volatile("fence.mbarrier_init.release.cluster;" ::: "memory");
    } else if (threadIdx.x >= 416 && threadIdx.x < 419) {
      asm volatile("prefetch.tensormap [%0];" ::"l"(threadIdx.x == 416 ? &mapQ : threadIdx.x == 417 ? &mapK : &mapV) : "memory");
    } else if (threadIdx.x == 448) {
      asm volatile("st.shared.v2.u32 [%0], {%1, %1};" ::"r"(pace_word), "r"(0) : "memory");
    }
    asm volatile("bar.sync 4, 128;" ::: "memory");
    cluster_arrive();
    asm volatile("setmaxnreg.dec.sync.aligned.u32 32;");
    const int pw = __shfl_sync(0xffffffffu, (int)(threadIdx.x >> 5) & 3, 0);
    if (pw >= 2) cluster_wait();

    if (pw == kIssuers) {
      if (rank == 0 && coresident) {
#pragma unroll 1
        for (int n = 0; n < (1 << 16); n++) {
          uint32_t seen, done;
          asm volatile("ld.relaxed.gpu.global.u32 %0, [%1];" : "=r"(seen) : "l"(&g_ticks) : "memory");
          asm volatile("st.volatile.shared.u32 [%0], %1;" ::"r"(pace_word), "r"(seen) : "memory");
          asm volatile("ld.volatile.shared.u32 %0, [%1];" : "=r"(done) : "r"(pace_word + 4) : "memory");
          if (done) break;
          __nanosleep(100);
        }
      }
    } else {
      const bool pacer = pw == 0 && rank == 0 && coresident;
      uint64_t pol_stream, pol_normal;
      asm volatile("createpolicy.fractional.L2::evict_first.b64 %0, 1.0;" : "=l"(pol_stream));
      asm volatile("createpolicy.fractional.L2::evict_normal.b64 %0, 1.0;" : "=l"(pol_normal));
      if (coresident) {
        const uint32_t delay = max(cid - kWarmClusters, 0) * kStaggerClocks;
        while ((uint32_t)clock() - t_entry < delay) __nanosleep(20);
      }
      int tick = 0;
#pragma unroll 1
      for (int i = pw; i < kLoads; i += kIssuers) {
        const uint32_t e = c_sched.prod[i];
        const uint32_t sl = e & 15u, kind = (e >> 5) & 3u;
        const uint32_t dst = base + sl * kSlotBytes, fb = bar_full + 8 * sl;
        const int row = (int)(e >> 12) * 64 + cid * kSeq, cb = (e >> 8) & 3u;
        mbar_wait(bar_empty + 8 * sl, ((e >> 4) & 1u) ^ 1u);
        if (pacer) {
          const int lead = kLeadEnd + kLeadExtra * min(max(kFadeEnd - tick, 0), kFadeEnd - kFadeBegin) / (kFadeEnd - kFadeBegin);
#pragma unroll 1
          for (int n = 0; n < 256; n++) {
            uint32_t seen;
            asm volatile("ld.volatile.shared.u32 %0, [%1];" : "=r"(seen) : "r"(pace_word) : "memory");
            if (tick * kClusters - (int)seen <= lead) break;
            __nanosleep(40);
          }
          tick++;
        }
        const uint64_t pol = i >= kStreamFrom ? pol_stream : pol_normal;
        if (kind == 0) tma_load(dst, &mapQ, fb, row + rank * 192, cb, pol);
        else tma_load_mc(dst + rank * 8192, kind == 1 ? &mapK : &mapV, fb, row + rank * 64, cb, pol);
        if (e & 128u) {
          const uint32_t en = c_sched.prod[i + kPrefAhead];
          tma_prefetch(&mapV, (int)(en >> 12) * 64 + cid * kSeq + rank * 64, (en >> 8) & 3u, pol_normal);
        }
        if (i < 2) cluster_wait();
        if (pacer && (threadIdx.x & 31) == 0)
          asm volatile("red.relaxed.gpu.global.inc.u32 [%0], %1;" ::"l"(&g_ticks), "r"(kTicks * kClusters - 1) : "memory");
      }
      if (pacer) asm volatile("st.volatile.shared.u32 [%0], %1;" ::"r"(pace_word + 4), "r"(1) : "memory");
    }
  } else {
    cluster_arrive();
    if (cid < kWarmClusters) {
      const size_t off = (size_t)cid * kHeadBytes + threadIdx.x * 128;
      prefetch_l2(gq + off + rank * 98304);
      prefetch_l2(gk + off + rank * 65536);
      prefetch_l2(gq + off + rank * 98304 + 49152);
      if (threadIdx.x < 128) prefetch_l2(gk + off + rank * 65536 + 49152);
    }
    asm volatile("setmaxnreg.inc.sync.aligned.u32 160;");
    const uint32_t lane = threadIdx.x & 31;
    const uint32_t dbase = desc_lo(base);
    const uint32_t rel_bar = map_to_cta(bar_empty, lane & 1);
    const int my_turn = 1 + wg, next_turn = 1 + (wg == 2 ? 0 : wg + 1);
    cluster_wait();
    if (wg == 2) turn_pass(1);
    const bool b0 = lane & 1, b1 = lane & 2;
    const uint32_t out_off =
        (uint32_t)(rank * 192 + wg * 64 + ((threadIdx.x >> 5) & 3) * 16 + (lane >> 2)) * 512u + (lane & 3) * 16u;

#pragma unroll 1
    for (int h = 0; h < kRounds; h++) {
      uint32_t P[96];
      float m[2], l[2];
      const uint32_t qw = c_sched.cons[h][8 + wg];

      auto qk_chunk = [&](auto jc) {
        constexpr int j = decltype(jc)::value;
        float s[64];
        const uint32_t kw = c_sched.cons[h][j];
        if (j == 0) wait_full(bar_full, qw);
        wait_full(bar_full, kw);
        turn_wait(my_turn);
#pragma unroll
        for (int cb = 0; cb < 4; cb++) {
          const uint32_t e = kw >> (8 * cb);
          bool ready = true;
          if (cb < 3) ready = test_full(bar_full, e >> 8);
          if (j == 0 && cb == 1) ready = ready && test_full(bar_full, qw >> 8);
          mma_qk(s, dbase + ((cb < 2 ? qw : qw >> 8) & 15u) * 1024 + (cb & 1) * 512, dbase + (e & 15u) * 1024, cb != 0);
          if (cb > 0) {
            wg_wait<1>();
            if (cb == 3) turn_pass(next_turn);
            release_slot(rel_bar, kw >> (8 * cb - 8), lane, 1);
            if (j == 2 && cb == 2) release_slot(rel_bar, qw, lane, 3);
          }
          if (!ready) {
            if (j == 0 && cb == 1) wait_full(bar_full, qw >> 8);
            wait_full(bar_full, e >> 8);
          }
        }
        wg_wait<0>();
        keep_regs(s);
        release_slot(rel_bar, kw >> 24, lane, 1);
        if (j == 2) release_slot(rel_bar, qw >> 8, lane, 3);
        softmax_chunk<j>(s, P, m, l);
      };
      qk_chunk(std::integral_constant<int, 0>{});
      qk_chunk(std::integral_constant<int, 1>{});
      qk_chunk(std::integral_constant<int, 2>{});
      l[0] += __shfl_xor_sync(0xffffffffu, l[0], 1);
      l[1] += __shfl_xor_sync(0xffffffffu, l[1], 1);
      l[0] += __shfl_xor_sync(0xffffffffu, l[0], 2);
      l[1] += __shfl_xor_sync(0xffffffffu, l[1], 2);
      const float inv0 = rcp(l[0]), inv1 = rcp(l[1]);

      char* optr = out + (size_t)(cid + h * kClusters) * kHeadBytes + out_off;
#pragma unroll 1
      for (int c = 0; c < 4; c++) {
        float o[32];
        const uint32_t vw = c_sched.cons[h][3 + c];
        wait_full(bar_full, vw);
        turn_wait(my_turn);
#pragma unroll
        for (int j = 0; j < 3; j++) {
          const uint32_t e = vw >> (8 * j);
          bool ready = true;
          if (j < 2) ready = test_full(bar_full, e >> 8);
          mma_pv(o, P + 32 * j, dbase + (e & 15u) * 1024, j != 0);
          if (j > 0) {
            wg_wait<1>();
            if (j == 2 && !(wg == 2 && c == 3 && h == kRounds - 1)) turn_pass(next_turn);
            release_slot(rel_bar, vw >> (8 * j - 8), lane, 1);
          }
          if (!ready) wait_full(bar_full, e >> 8);
        }
        wg_wait<0>();
        keep_regs(o);
        release_slot(rel_bar, vw >> 16, lane, 1);
#pragma unroll
        for (int q = 0; q < 2; q++) {
#pragma unroll
          for (int r = 0; r < 2; r++) {
            const int b = 16 * q + 2 * r;
            const float f = r ? inv1 : inv0;
            *reinterpret_cast<uint4*>(optr + r * 4096 + q * 64) =
                quad_transpose(pack_bf16(o[b] * f, o[b + 1] * f), pack_bf16(o[b + 4] * f, o[b + 5] * f),
                               pack_bf16(o[b + 8] * f, o[b + 9] * f), pack_bf16(o[b + 12] * f, o[b + 13] * f), b0, b1);
          }
        }
        optr += 128;
      }
    }
  }
}

typedef CUresult (*EncodeTiledFn)(CUtensorMap*, CUtensorMapDataType, cuuint32_t, void*, const cuuint64_t*,
                                  const cuuint64_t*, const cuuint32_t*, const cuuint32_t*, CUtensorMapInterleave,
                                  CUtensorMapSwizzle, CUtensorMapL2promotion, CUtensorMapFloatOOBfill);

CUtensorMap make_map(EncodeTiledFn enc, const void* ptr, uint32_t boxBlocks) {
  CUtensorMap m;
  cuuint64_t dims[3] = {64, (cuuint64_t)kHeads * kSeq, 4};
  cuuint64_t strides[2] = {512, 128};
  cuuint32_t box[3] = {64, 64, boxBlocks};
  cuuint32_t es[3] = {1, 1, 1};
  enc(&m, CU_TENSOR_MAP_DATA_TYPE_BFLOAT16, 3, const_cast<void*>(ptr), dims, strides, box, es,
      CU_TENSOR_MAP_INTERLEAVE_NONE, CU_TENSOR_MAP_SWIZZLE_128B, CU_TENSOR_MAP_L2_PROMOTION_L2_128B,
      CU_TENSOR_MAP_FLOAT_OOB_FILL_NONE);
  return m;
}

}

extern "C" void kernel_launch(void* const* d_in, const int* in_sizes, int n_in, void* d_out, int out_size) {
  static EncodeTiledFn enc = nullptr;
  static int coresident = 0;
  if (!enc) {
    void* fn = nullptr;
    cudaDriverEntryPointQueryResult qr;
    cudaGetDriverEntryPoint("cuTensorMapEncodeTiled", &fn, cudaEnableDefault, &qr);
    enc = (EncodeTiledFn)fn;
    cudaFuncSetAttribute(mha_kernel, cudaFuncAttributeMaxDynamicSharedMemorySize, kSmemBytes);
    cudaLaunchConfig_t cfg = {};
    cfg.gridDim = dim3(2 * kClusters), cfg.blockDim = dim3(kThreads), cfg.dynamicSmemBytes = kSmemBytes;
    cudaLaunchAttribute attr;
    attr.id = cudaLaunchAttributeClusterDimension;
    attr.val.clusterDim.x = 2, attr.val.clusterDim.y = 1, attr.val.clusterDim.z = 1;
    cfg.attrs = &attr, cfg.numAttrs = 1;
    int clusters = 0;
    if (cudaOccupancyMaxActiveClusters(&clusters, mha_kernel, &cfg) != cudaSuccess) clusters = 0, (void)cudaGetLastError();
    coresident = clusters >= kClusters;
  }
  const CUtensorMap mq = make_map(enc, d_in[0], 2);
  const CUtensorMap mk = make_map(enc, d_in[1], 1);
  const CUtensorMap mv = make_map(enc, d_in[2], 1);
  mha_kernel<<<2 * kClusters, kThreads, kSmemBytes, cudaStreamPerThread>>>(
      mq, mk, mv, (const char*)d_in[0], (const char*)d_in[1], (char*)d_out, coresident);
}
```

```cpp
#include <cuda_runtime.h>
#include <cuda_bf16.h>
#include <cuda.h>
#include <stdint.h>
#include <type_traits>

namespace {

constexpr int kSeq = 384;
constexpr int kHeads = 512;
constexpr int kHeadBytes = kSeq * 512;
constexpr int kClusters = 64;
constexpr int kRounds = kHeads / kClusters;
constexpr int kSlots = 14;
constexpr int kSlotBytes = 16384;
constexpr int kUnits = 30;
constexpr int kLoads = kRounds * kUnits;
constexpr int kThreads = 512;
constexpr int kSmemBytes = kSlots * kSlotBytes + 1024   + 1024  ;
constexpr uint32_t kEmptyCount = 24;

constexpr int kIssuers = 3;
constexpr int kFirstClusters = 9;
constexpr int kStaggerClocks = 220;
constexpr int kStreamFrom = 190;
constexpr int kPrefBegin = 14, kPrefEnd = 22;
constexpr int kPrefAhead = 4;
constexpr int kPrefUntil = 150;
constexpr int kTicks = (kLoads - kSlots + kIssuers - 1) / kIssuers;
constexpr int kLeadEnd = 105;
constexpr int kLeadExtra = 130;
constexpr int kFadeBegin = 35, kFadeEnd = 65;

constexpr int kIdx(int u) { return u < 4 ? 2 + u : 6 + u; }
constexpr int qIdx(int w, int h) { return w == 0 ? h : 4 + 2 * w + h; }
struct Sched {
  uint32_t cons[kRounds][12];
  uint32_t prod[kLoads];
};
constexpr Sched makeSched() {
  Sched s{};
  int rel[kUnits] = {};
  int n = 0;
  for (int g = 0; g < 3; g++)
    for (int w = 0; w < 3; w++)
      for (int a = 0; a < 4; a++) {
        if (w == 2) rel[n++] = kIdx(g * 4 + a);
        if (g == 2 && (a & 1)) rel[n++] = qIdx(w, a / 2);
      }
  for (int x = 0; x < 12; x++) rel[n++] = 18 + x;
  const int last_v[12] = {4, 5, 6, 8, 9, 10, 12, 13, 15, 18, 19, 20};
  int slot[kLoads] = {};
  uint32_t ent[kRounds][kUnits] = {};
  int uses[kSlots] = {};
  for (int i = 0; i < kLoads; i++) {
    const int h = i / kUnits, u = i % kUnits;
    int sl = i;
    if (i >= kSlots) {
      const int k = (h == kRounds - 1 && u >= 18) ? h * kUnits + last_v[u - 18] : i - kSlots;
      const int prev = (k / kUnits) * kUnits + rel[k % kUnits];
      sl = slot[prev];
      ent[prev / kUnits][prev % kUnits] |= 32u;
    }
    slot[i] = sl;
    ent[h][u] = (uint32_t)(sl | ((uses[sl]++ & 1) << 4));
    int kind = 0, cb = 0, r64 = 0;
    if (u < 2 || (u >= 6 && u < 10)) {
      cb = (u & 1) * 2, r64 = u < 2 ? 0 : (u - 4) / 2;
    } else if (u < 18) {
      const int ku = u < 6 ? u - 2 : u - 6;
      kind = 1, cb = ku & 3, r64 = (ku / 4) * 2;
    } else {
      kind = 2, cb = (u - 18) / 3, r64 = ((u - 18) % 3) * 2;
    }
    const int pref = u >= kPrefBegin && u < kPrefEnd && i < kPrefUntil;
    s.prod[i] = ent[h][u] | (uint32_t)(kind << 5) | (uint32_t)(pref << 7) | (uint32_t)(cb << 8) |
                (uint32_t)((h * kClusters * 6 + r64) << 12);
  }
  for (int h = 0; h < kRounds; h++) {
    for (int g = 0; g < 3; g++)
      for (int a = 0; a < 4; a++) s.cons[h][g] |= ent[h][kIdx(g * 4 + a)] << (8 * a);
    for (int c = 0; c < 4; c++)
      for (int a = 0; a < 3; a++) s.cons[h][3 + c] |= ent[h][18 + c * 3 + a] << (8 * a);
    for (int w = 0; w < 3; w++)
      for (int a = 0; a < 2; a++) s.cons[h][8 + w] |= ent[h][qIdx(w, a)] << (8 * a);
  }
  return s;
}
static_assert(kPrefBegin + kPrefAhead >= 18 && kPrefEnd - 1 + kPrefAhead < kUnits, "prefetch targets must be V tiles");
__constant__ Sched c_sched = makeSched();

__host__ __device__ constexpr uint32_t first_entry(int i) {
  const bool q = (0x3C3 >> i) & 1;
  const int ku = i < 6 ? i - 2 : i - 6;
  return (uint32_t)(i | (q ? ((i & 1) << 9) | ((i < 2 ? 0 : (i - 4) >> 1) << 12) : 32 | ((ku & 3) << 8) | ((ku >> 2) << 13)));
}
constexpr bool first_entries_ok() {
  const Sched s = makeSched();
  for (int i = 0; i < kSlots; i++)
    if (s.prod[i] != first_entry(i)) return false;
  return true;
}
static_assert(first_entries_ok(), "first_entry() must match the schedule table");

__device__ unsigned int g_ticks;

__device__ __forceinline__ uint32_t smem_u32(const void* p) { return (uint32_t)__cvta_generic_to_shared(p); }
__device__ __forceinline__ void mbar_init(uint32_t bar, uint32_t cnt) {
  asm volatile("mbarrier.init.shared::cta.b64 [%0], %1;" ::"r"(bar), "r"(cnt) : "memory");
}
__device__ __forceinline__ void mbar_wait(uint32_t bar, uint32_t parity) {
  asm volatile(
      "{\n"
      ".reg .pred p;\n"
      ".reg .u32 n;\n"
      "mov.u32 n, 0;\n"
      "LAB_WAIT:\n"
      "mbarrier.try_wait.parity.shared::cta.b64 p, [%0], %1;\n"
      "@p bra LAB_DONE;\n"
      "add.u32 n, n, 1;\n"
      "setp.lt.u32 p, n, 0x80000;\n"
      "@p bra LAB_WAIT;\n"
      "trap;\n"
      "LAB_DONE:\n"
      "}\n" ::"r"(bar),
      "r"(parity)
      : "memory");
}
__device__ __forceinline__ bool mbar_test(uint32_t bar, uint32_t parity) {
  uint32_t ok;
  asm volatile("{\n.reg .pred p;\nmbarrier.test_wait.parity.shared::cta.b64 p, [%1], %2;\nselp.u32 %0, 1, 0, p;\n}\n"
               : "=r"(ok)
               : "r"(bar), "r"(parity)
               : "memory");
  return ok;
}
__device__ __forceinline__ void wait_full(uint32_t bars, uint32_t entry) { mbar_wait(bars + 8 * (entry & 15u), (entry >> 4) & 1u); }
__device__ __forceinline__ bool test_full(uint32_t bars, uint32_t entry) { return mbar_test(bars + 8 * (entry & 15u), (entry >> 4) & 1u); }
__device__ __forceinline__ uint32_t map_to_cta(uint32_t addr, uint32_t cta) {
  uint32_t r;
  asm("mapa.shared::cluster.u32 %0, %1, %2;" : "=r"(r) : "r"(addr), "r"(cta));
  return r;
}
__device__ __forceinline__ void release_slot(uint32_t bars, uint32_t entry, uint32_t lane, uint32_t count) {
  asm volatile(
      "{\n"
      ".reg .pred p;\n"
      "setp.lt.u32 p, %1, %3;\n"
      "@p mbarrier.arrive.shared::cluster.b64 _, [%0], %2;\n"
      "}\n" ::"r"(bars + 8 * (entry & 15u)),
      "r"(lane), "r"(count), "r"((entry >> 4) & 2u)
      : "memory");
}
__device__ __forceinline__ void tma_load(uint32_t dst, const CUtensorMap* m, uint32_t bar, int row, int cb, uint64_t pol) {
  asm volatile(
      "{\n.reg .pred p;\nelect.sync _|p, 0xffffffff;\n"
      "@p mbarrier.arrive.expect_tx.shared::cta.b64 _, [%2], 16384;\n"
      "@p cp.async.bulk.tensor.3d.shared::cluster.global.mbarrier::complete_tx::bytes.L2::cache_hint"
      " [%0], [%1, {%3, %4, %5}], [%2], %6;\n}\n" ::"r"(dst),
      "l"(m), "r"(bar), "r"(0), "r"(row), "r"(cb), "l"(pol)
      : "memory");
}
__device__ __forceinline__ void tma_load_mc(uint32_t dst, const CUtensorMap* m, uint32_t bar, int row, int cb, uint64_t pol) {
  asm volatile(
      "{\n.reg .pred p;\nelect.sync _|p, 0xffffffff;\n"
      "@p mbarrier.arrive.expect_tx.shared::cta.b64 _, [%2], 16384;\n"
      "@p cp.async.bulk.tensor.3d.shared::cluster.global.mbarrier::complete_tx::bytes.multicast::cluster.L2::cache_hint"
      " [%0], [%1, {%3, %4, %5}], [%2], %6, %7;\n}\n" ::"r"(dst),
      "l"(m), "r"(bar), "r"(0), "r"(row), "r"(cb), "h"((uint16_t)3), "l"(pol)
      : "memory");
}
__device__ __forceinline__ void tma_prefetch(const CUtensorMap* m, int row, int cb, uint64_t pol) {
  asm volatile(
      "{\n.reg .pred p;\nelect.sync _|p, 0xffffffff;\n"
      "@p cp.async.bulk.prefetch.tensor.3d.L2.global.L2::cache_hint [%0, {%1, %2, %3}], %4;\n}\n" ::"l"(m),
      "r"(0), "r"(row), "r"(cb), "l"(pol)
      : "memory");
}
__device__ __forceinline__ void cluster_arrive() { asm volatile("barrier.cluster.arrive.relaxed.aligned;" ::: "memory"); }
__device__ __forceinline__ void cluster_wait() { asm volatile("barrier.cluster.wait.aligned;" ::: "memory"); }
__device__ __forceinline__ void turn_wait(int id) { asm volatile("bar.sync %0, 256;" ::"r"(id) : "memory"); }
__device__ __forceinline__ void turn_pass(int id) { asm volatile("bar.arrive %0, 256;" ::"r"(id) : "memory"); }
template <int N>
__device__ __forceinline__ void wg_wait() {
  asm volatile("wgmma.wait_group.sync.aligned %0;" ::"n"(N) : "memory");
}
__device__ __forceinline__ float ex2(float x) {
  float y;
  asm("ex2.approx.ftz.f32 %0, %1;" : "=f"(y) : "f"(x));
  return y;
}
__device__ __forceinline__ float rcp(float x) {
  float y;
  asm("rcp.approx.ftz.f32 %0, %1;" : "=f"(y) : "f"(x));
  return y;
}
__device__ __forceinline__ uint32_t pack_bf16(float lo, float hi) {
  uint32_t r;
  asm("cvt.rn.bf16x2.f32 %0, %1, %2;" : "=r"(r) : "f"(hi), "f"(lo));
  return r;
}
__device__ __forceinline__ void scale_bf16x2(uint32_t& x, uint32_t fh, uint32_t fl) {
  asm("{\n.reg .b32 t;\nmul.rn.bf16x2 t, %0, %2;\nfma.rn.bf16x2 %0, %0, %1, t;\n}\n" : "+r"(x) : "r"(fh), "r"(fl));
}

constexpr uint32_t kDescHi = 64u | (1u << 30);
__device__ __forceinline__ uint32_t desc_lo(uint32_t addr) { return ((addr & 0x3FFFF) >> 4) | (1u << 16); }

#define ACC8(a, o) \
  "+f"(a[o]), "+f"(a[o + 1]), "+f"(a[o + 2]), "+f"(a[o + 3]), "+f"(a[o + 4]), "+f"(a[o + 5]), "+f"(a[o + 6]), "+f"(a[o + 7])
#define IN8(a, o) \
  "r"(a[o]), "r"(a[o + 1]), "r"(a[o + 2]), "r"(a[o + 3]), "r"(a[o + 4]), "r"(a[o + 5]), "r"(a[o + 6]), "r"(a[o + 7])
#define REGS32 "{%0,%1,%2,%3,%4,%5,%6,%7,%8,%9,%10,%11,%12,%13,%14,%15,%16,%17,%18,%19,%20,%21,%22,%23,%24,%25,%26,%27,%28,%29,%30,%31}"
#define REGS64 "{%0,%1,%2,%3,%4,%5,%6,%7,%8,%9,%10,%11,%12,%13,%14,%15,%16,%17,%18,%19,%20,%21,%22,%23,%24,%25,%26,%27,%28,%29,%30,%31,%32,%33,%34,%35,%36,%37,%38,%39,%40,%41,%42,%43,%44,%45,%46,%47,%48,%49,%50,%51,%52,%53,%54,%55,%56,%57,%58,%59,%60,%61,%62,%63}"

__device__ __forceinline__ void mma_qk(float (&d)[64], uint32_t qa, uint32_t kb, int accumulate) {
  asm volatile(
      "{\n.reg .pred p;\n.reg .b32 a, b;\n.reg .b64 da, db;\n"
      "setp.ne.b32 p, %66, 0;\n"
      "wgmma.fence.sync.aligned;\n"
      "mov.b64 da, {%64, %67};\nmov.b64 db, {%65, %67};\n"
      "wgmma.mma_async.sync.aligned.m64n128k16.f32.bf16.bf16 " REGS64 ", da, db, p, 1, 1, 0, 0;\n"
      "add.u32 a, %64, 2;\nadd.u32 b, %65, 2;\nmov.b64 da, {a, %67};\nmov.b64 db, {b, %67};\n"
      "wgmma.mma_async.sync.aligned.m64n128k16.f32.bf16.bf16 " REGS64 ", da, db, 1, 1, 1, 0, 0;\n"
      "add.u32 a, %64, 4;\nadd.u32 b, %65, 4;\nmov.b64 da, {a, %67};\nmov.b64 db, {b, %67};\n"
      "wgmma.mma_async.sync.aligned.m64n128k16.f32.bf16.bf16 " REGS64 ", da, db, 1, 1, 1, 0, 0;\n"
      "add.u32 a, %64, 6;\nadd.u32 b, %65, 6;\nmov.b64 da, {a, %67};\nmov.b64 db, {b, %67};\n"
      "wgmma.mma_async.sync.aligned.m64n128k16.f32.bf16.bf16 " REGS64 ", da, db, 1, 1, 1, 0, 0;\n"
      "wgmma.commit_group.sync.aligned;\n}\n"
      : ACC8(d, 0), ACC8(d, 8), ACC8(d, 16), ACC8(d, 24), ACC8(d, 32), ACC8(d, 40), ACC8(d, 48), ACC8(d, 56)
      : "r"(qa), "r"(kb), "r"(accumulate), "n"(kDescHi)
      : "memory");
}
__device__ __forceinline__ void mma_pv(float (&d)[32], const uint32_t* a, uint32_t vb, int accumulate) {
  asm volatile(
      "{\n.reg .pred p;\n.reg .b32 b;\n.reg .b64 db;\n"
      "setp.ne.b32 p, %65, 0;\n"
      "wgmma.fence.sync.aligned;\n"
      "mov.b64 db, {%64, %66};\n"
      "wgmma.mma_async.sync.aligned.m64n64k16.f32.bf16.bf16 " REGS32 ", {%32,%33,%34,%35}, db, p, 1, 1, 1;\n"
      "add.u32 b, %64, 128;\nmov.b64 db, {b, %66};\n"
      "wgmma.mma_async.sync.aligned.m64n64k16.f32.bf16.bf16 " REGS32 ", {%36,%37,%38,%39}, db, 1, 1, 1, 1;\n"
      "add.u32 b, %64, 256;\nmov.b64 db, {b, %66};\n"
      "wgmma.mma_async.sync.aligned.m64n64k16.f32.bf16.bf16 " REGS32 ", {%40,%41,%42,%43}, db, 1, 1, 1, 1;\n"
      "add.u32 b, %64, 384;\nmov.b64 db, {b, %66};\n"
      "wgmma.mma_async.sync.aligned.m64n64k16.f32.bf16.bf16 " REGS32 ", {%44,%45,%46,%47}, db, 1, 1, 1, 1;\n"
      "add.u32 b, %64, 512;\nmov.b64 db, {b, %66};\n"
      "wgmma.mma_async.sync.aligned.m64n64k16.f32.bf16.bf16 " REGS32 ", {%48,%49,%50,%51}, db, 1, 1, 1, 1;\n"
      "add.u32 b, %64, 640;\nmov.b64 db, {b, %66};\n"
      "wgmma.mma_async.sync.aligned.m64n64k16.f32.bf16.bf16 " REGS32 ", {%52,%53,%54,%55}, db, 1, 1, 1, 1;\n"
      "add.u32 b, %64, 768;\nmov.b64 db, {b, %66};\n"
      "wgmma.mma_async.sync.aligned.m64n64k16.f32.bf16.bf16 " REGS32 ", {%56,%57,%58,%59}, db, 1, 1, 1, 1;\n"
      "add.u32 b, %64, 896;\nmov.b64 db, {b, %66};\n"
      "wgmma.mma_async.sync.aligned.m64n64k16.f32.bf16.bf16 " REGS32 ", {%60,%61,%62,%63}, db, 1, 1, 1, 1;\n"
      "wgmma.commit_group.sync.aligned;\n}\n"
      : ACC8(d, 0), ACC8(d, 8), ACC8(d, 16), ACC8(d, 24)
      : IN8(a, 0), IN8(a, 8), IN8(a, 16), IN8(a, 24), "r"(vb), "r"(accumulate), "n"(kDescHi)
      : "memory");
}
template <int N>
__device__ __forceinline__ void keep_regs(float (&d)[N]) {
#pragma unroll
  for (int i = 0; i < N; i++) asm volatile("" : "+f"(d[i])::"memory");
}

__device__ __forceinline__ uint4 quad_transpose(uint32_t a0, uint32_t a1, uint32_t a2, uint32_t a3, bool b0, bool b1) {
  uint32_t s0 = b0 ? a0 : a1, s1 = b0 ? a2 : a3;
  uint32_t r0 = __shfl_xor_sync(0xffffffffu, s0, 1), r1 = __shfl_xor_sync(0xffffffffu, s1, 1);
  uint32_t c0 = b0 ? r0 : a0, c1 = b0 ? a1 : r0, c2 = b0 ? r1 : a2, c3 = b0 ? a3 : r1;
  uint32_t t0 = b1 ? c0 : c2, t1 = b1 ? c1 : c3;
  uint32_t u0 = __shfl_xor_sync(0xffffffffu, t0, 2), u1 = __shfl_xor_sync(0xffffffffu, t1, 2);
  uint4 r;
  r.x = b1 ? u0 : c0;
  r.y = b1 ? u1 : c1;
  r.z = b1 ? c2 : u0;
  r.w = b1 ? c3 : u1;
  return r;
}

constexpr float kScaleLog2 = 0.0625f * 1.4426950408889634f;
constexpr float kRescaleThreshold = 8.f;

template <int N>
__device__ __forceinline__ void rescale_p(uint32_t* P, float f0, float f1) {
  const uint32_t h0 = pack_bf16(f0, f0), h1 = pack_bf16(f1, f1);
  const float r0 = f0 - __uint_as_float(h0 << 16), r1 = f1 - __uint_as_float(h1 << 16);
  const uint32_t l0 = pack_bf16(r0, r0), l1 = pack_bf16(r1, r1);
#pragma unroll
  for (int i = 0; i < N / 2; i++) {
    scale_bf16x2(P[2 * i], h0, l0);
    scale_bf16x2(P[2 * i + 1], h1, l1);
  }
}
__device__ __forceinline__ void row_max_float(const float (&s)[64], float& mx0, float& mx1) {
  mx0 = fmaxf(s[0], s[1]), mx1 = fmaxf(s[2], s[3]);
#pragma unroll
  for (int i = 1; i < 16; i++) {
    mx0 = fmaxf(mx0, fmaxf(s[4 * i], s[4 * i + 1]));
    mx1 = fmaxf(mx1, fmaxf(s[4 * i + 2], s[4 * i + 3]));
  }
  mx0 = fmaxf(mx0, __shfl_xor_sync(0xffffffffu, mx0, 1));
  mx1 = fmaxf(mx1, __shfl_xor_sync(0xffffffffu, mx1, 1));
  mx0 = fmaxf(mx0, __shfl_xor_sync(0xffffffffu, mx0, 2));
  mx1 = fmaxf(mx1, __shfl_xor_sync(0xffffffffu, mx1, 2));
}
__device__ __forceinline__ void row_max_int(const float (&s)[64], float& mx0, float& mx1) {
  int a0 = max(__float_as_int(s[0]), __float_as_int(s[1])), a1 = max(__float_as_int(s[2]), __float_as_int(s[3]));
  int b0 = max(__float_as_int(s[4]), __float_as_int(s[5])), b1 = max(__float_as_int(s[6]), __float_as_int(s[7]));
#pragma unroll
  for (int i = 1; i < 8; i++) {
    a0 = __vimax3_s32(a0, __float_as_int(s[8 * i]), __float_as_int(s[8 * i + 1]));
    a1 = __vimax3_s32(a1, __float_as_int(s[8 * i + 2]), __float_as_int(s[8 * i + 3]));
    b0 = __vimax3_s32(b0, __float_as_int(s[8 * i + 4]), __float_as_int(s[8 * i + 5]));
    b1 = __vimax3_s32(b1, __float_as_int(s[8 * i + 6]), __float_as_int(s[8 * i + 7]));
  }
  a0 = max(a0, b0);
  a1 = max(a1, b1);
  a0 = max(a0, __shfl_xor_sync(0xffffffffu, a0, 1));
  a1 = max(a1, __shfl_xor_sync(0xffffffffu, a1, 1));
  a0 = max(a0, __shfl_xor_sync(0xffffffffu, a0, 2));
  a1 = max(a1, __shfl_xor_sync(0xffffffffu, a1, 2));
  mx0 = __int_as_float(a0);
  mx1 = __int_as_float(a1);
}

template <int J>
__device__ __forceinline__ void softmax_chunk(float (&s)[64], uint32_t (&P)[96], float (&m)[2], float (&l)[2]) {
  float mx0, mx1;
  row_max_int(s, mx0, mx1);
  bool redo = (__float_as_int(mx0) | __float_as_int(mx1)) < 0;
  if (J > 0)
    redo = redo || fmaf(mx0, kScaleLog2, -m[0]) > kRescaleThreshold || fmaf(mx1, kScaleLog2, -m[1]) > kRescaleThreshold;
  if (__any_sync(0xffffffffu, redo)) {
    row_max_float(s, mx0, mx1);
    if (J > 0) {
      const float n0 = fmaxf(m[0], mx0 * kScaleLog2), n1 = fmaxf(m[1], mx1 * kScaleLog2);
      const float f0 = ex2(m[0] - n0), f1 = ex2(m[1] - n1);
      rescale_p<32 * J>(P, f0, f1);
      l[0] *= f0, l[1] *= f1;
      m[0] = n0, m[1] = n1;
    }
  }
  if (J == 0) m[0] = mx0 * kScaleLog2, m[1] = mx1 * kScaleLog2;
  float a0 = J ? l[0] : 0.f, a1 = J ? l[1] : 0.f, b0 = 0.f, b1 = 0.f;
#pragma unroll
  for (int ii = 0; ii < 16; ii++) {
    const int i = ii ^ 8;
    s[4 * i] = ex2(fmaf(s[4 * i], kScaleLog2, -m[0]));
    s[4 * i + 1] = ex2(fmaf(s[4 * i + 1], kScaleLog2, -m[0]));
    s[4 * i + 2] = ex2(fmaf(s[4 * i + 2], kScaleLog2, -m[1]));
    s[4 * i + 3] = ex2(fmaf(s[4 * i + 3], kScaleLog2, -m[1]));
    a0 += s[4 * i];
    b0 += s[4 * i + 1];
    a1 += s[4 * i + 2];
    b1 += s[4 * i + 3];
    P[32 * J + 2 * i] = pack_bf16(s[4 * i], s[4 * i + 1]);
    P[32 * J + 2 * i + 1] = pack_bf16(s[4 * i + 2], s[4 * i + 3]);
  }
  l[0] = a0 + b0;
  l[1] = a1 + b1;
}

__global__ void __cluster_dims__(2, 1, 1) __launch_bounds__(kThreads, 1)
    mha_kernel(char* __restrict__ out, unsigned int* ticks, const int coresident, const __grid_constant__ CUtensorMap mapQ,
               const __grid_constant__ CUtensorMap mapK, const __grid_constant__ CUtensorMap mapV) {
  extern __shared__ unsigned char smem_raw[];
  const uint32_t base = (smem_u32(smem_raw) + 1023u) & ~1023u;
  const uint32_t bar_full = base + kSlots * kSlotBytes;
  const uint32_t bar_empty = bar_full + 128;
  const int wg = __shfl_sync(0xffffffffu, (int)(threadIdx.x >> 7), 0);
  const int rank = blockIdx.x & 1;
  const int cid = blockIdx.x >> 1;

  if (wg == 3) {
    const uint32_t t_entry = clock();
    const uint32_t pace_word = bar_full + 256;
    const int pw = __shfl_sync(0xffffffffu, (int)(threadIdx.x >> 5) & 3, 0);
    if ((threadIdx.x & 31) == 0) {
      if (pw < 2) {
#pragma unroll
        for (int i = 0; i < kSlots; i++) mbar_init((pw ? bar_empty : bar_full) + 8 * i, pw ? kEmptyCount : 1);
        asm volatile("fence.mbarrier_init.release.cluster;" ::: "memory");
      } else if (pw == 2) {
        asm volatile("prefetch.tensormap [%0];" ::"l"(&mapQ) : "memory");
        asm volatile("prefetch.tensormap [%0];" ::"l"(&mapK) : "memory");
        asm volatile("prefetch.tensormap [%0];" ::"l"(&mapV) : "memory");
      } else {
        asm volatile("st.shared.v2.u32 [%0], {%1, %1};" ::"r"(pace_word), "r"(0) : "memory");
      }
    }
    asm volatile("bar.sync 4, 128;" ::: "memory");
    cluster_arrive();
    uint64_t pol_stream, pol_normal;
    asm volatile("createpolicy.fractional.L2::evict_normal.b64 %0, 1.0;" : "=l"(pol_normal));
    auto issue = [&](uint32_t e, uint64_t pol) {
      const uint32_t sl = e & 15u, kind = (e >> 5) & 3u;
      const uint32_t dst = base + sl * kSlotBytes, fb = bar_full + 8 * sl;
      const int row = (int)(e >> 12) * 64 + cid * kSeq, cb = (e >> 8) & 3u;
      if (kind == 0) tma_load(dst, &mapQ, fb, row + rank * 192, cb, pol);
      else tma_load_mc(dst + rank * 8192, kind == 1 ? &mapK : &mapV, fb, row + rank * 64, cb, pol);
    };
    if (pw >= 2) cluster_wait();
    if (coresident) {
      const uint32_t delay = max(cid - kFirstClusters, 0) * kStaggerClocks;
      while ((uint32_t)clock() - t_entry < delay) __nanosleep(20);
    }
#pragma unroll 1
    for (int i = pw; i < kSlots; i += 4) {
      issue(first_entry(i), pol_normal);
      if (i < 2) cluster_wait();
    }
    asm volatile("setmaxnreg.dec.sync.aligned.u32 32;");

    if (pw == kIssuers) {
      if (rank == 0 && coresident) {
#pragma unroll 1
        for (int n = 0; n < (1 << 16); n++) {
          uint32_t seen, done;
          asm volatile("ld.relaxed.gpu.global.u32 %0, [%1];" : "=r"(seen) : "l"(ticks) : "memory");
          asm volatile("st.volatile.shared.u32 [%0], %1;" ::"r"(pace_word), "r"(seen) : "memory");
          asm volatile("ld.volatile.shared.u32 %0, [%1];" : "=r"(done) : "r"(pace_word + 4) : "memory");
          if (done) break;
          __nanosleep(100);
        }
      }
    } else {
      const bool pacer = pw == 0 && rank == 0 && coresident;
      asm volatile("createpolicy.fractional.L2::evict_first.b64 %0, 1.0;" : "=l"(pol_stream));
      int tick = 0, patience = 512;
#pragma unroll 1
      for (int i = kSlots + pw; i < kLoads; i += kIssuers) {
        const uint32_t e = c_sched.prod[i];
        mbar_wait(bar_empty + 8 * (e & 15u), ((e >> 4) & 1u) ^ 1u);
        if (pacer) {
          const int lead = kLeadEnd + kLeadExtra * min(max(kFadeEnd - tick, 0), kFadeEnd - kFadeBegin) / (kFadeEnd - kFadeBegin);
#pragma unroll 1
          for (; patience > 0; patience--) {
            uint32_t seen;
            asm volatile("ld.volatile.shared.u32 %0, [%1];" : "=r"(seen) : "r"(pace_word) : "memory");
            if (tick * kClusters - (int)seen <= lead) break;
            __nanosleep(40);
          }
          tick++;
        }
        issue(e, i >= kStreamFrom ? pol_stream : pol_normal);
        if (e & 128u) {
          const uint32_t en = c_sched.prod[i + kPrefAhead];
          tma_prefetch(&mapV, (int)(en >> 12) * 64 + cid * kSeq + rank * 64, (en >> 8) & 3u, pol_normal);
        }
        if (pacer && (threadIdx.x & 31) == 0)
          asm volatile("red.relaxed.gpu.global.inc.u32 [%0], %1;" ::"l"(ticks), "r"(kTicks * kClusters - 1) : "memory");
      }
      if (pacer) asm volatile("st.volatile.shared.u32 [%0], %1;" ::"r"(pace_word + 4), "r"(1) : "memory");
    }
  } else {
    cluster_arrive();
    asm volatile("setmaxnreg.inc.sync.aligned.u32 160;");
    const uint32_t lane = threadIdx.x & 31;
    const uint32_t dbase = desc_lo(base);
    const uint32_t rel_bar = map_to_cta(bar_empty, lane & 1);
    const int my_turn = 1 + wg, next_turn = 1 + (wg == 2 ? 0 : wg + 1);
    cluster_wait();
    if (wg == 2) turn_pass(1);
    const bool b0 = lane & 1, b1 = lane & 2;
    const uint32_t out_off =
        (uint32_t)(rank * 192 + wg * 64 + ((threadIdx.x >> 5) & 3) * 16 + (lane >> 2)) * 512u + (lane & 3) * 16u;

#pragma unroll 1
    for (int h = 0; h < kRounds; h++) {
      uint32_t P[96];
      float m[2], l[2];
      const uint32_t qw = c_sched.cons[h][8 + wg];

      auto qk_chunk = [&](auto jc) {
        constexpr int j = decltype(jc)::value;
        float s[64];
        const uint32_t kw = c_sched.cons[h][j];
        if (j == 0) wait_full(bar_full, qw);
        wait_full(bar_full, kw);
        turn_wait(my_turn);
#pragma unroll
        for (int cb = 0; cb < 4; cb++) {
          const uint32_t e = kw >> (8 * cb);
          bool ready = true;
          if (cb < 3) ready = test_full(bar_full, e >> 8);
          if (j == 0 && cb == 1) ready = ready && test_full(bar_full, qw >> 8);
          mma_qk(s, dbase + ((cb < 2 ? qw : qw >> 8) & 15u) * 1024 + (cb & 1) * 512, dbase + (e & 15u) * 1024, cb != 0);
          if (cb > 0) {
            wg_wait<1>();
            if (cb == 3) turn_pass(next_turn);
            release_slot(rel_bar, kw >> (8 * cb - 8), lane, 1);
            if (j == 2 && cb == 2) release_slot(rel_bar, qw, lane, 3);
          }
          if (!ready) {
            if (j == 0 && cb == 1) wait_full(bar_full, qw >> 8);
            wait_full(bar_full, e >> 8);
          }
        }
        wg_wait<0>();
        keep_regs(s);
        release_slot(rel_bar, kw >> 24, lane, 1);
        if (j == 2) release_slot(rel_bar, qw >> 8, lane, 3);
        softmax_chunk<j>(s, P, m, l);
      };
      qk_chunk(std::integral_constant<int, 0>{});
      qk_chunk(std::integral_constant<int, 1>{});
      qk_chunk(std::integral_constant<int, 2>{});
      l[0] += __shfl_xor_sync(0xffffffffu, l[0], 1);
      l[1] += __shfl_xor_sync(0xffffffffu, l[1], 1);
      l[0] += __shfl_xor_sync(0xffffffffu, l[0], 2);
      l[1] += __shfl_xor_sync(0xffffffffu, l[1], 2);
      const float inv0 = rcp(l[0]), inv1 = rcp(l[1]);

      char* optr = out + (size_t)(cid + h * kClusters) * kHeadBytes + out_off;
#pragma unroll 1
      for (int c = 0; c < 4; c++) {
        float o[32];
        const uint32_t vw = c_sched.cons[h][3 + c];
        wait_full(bar_full, vw);
        turn_wait(my_turn);
#pragma unroll
        for (int j = 0; j < 3; j++) {
          const uint32_t e = vw >> (8 * j);
          bool ready = true;
          if (j < 2) ready = test_full(bar_full, e >> 8);
          mma_pv(o, P + 32 * j, dbase + (e & 15u) * 1024, j != 0);
          if (j > 0) {
            wg_wait<1>();
            if (j == 2 && !(wg == 2 && c == 3 && h == kRounds - 1)) turn_pass(next_turn);
            release_slot(rel_bar, vw >> (8 * j - 8), lane, 1);
          }
          if (!ready) wait_full(bar_full, e >> 8);
        }
        wg_wait<0>();
        keep_regs(o);
        release_slot(rel_bar, vw >> 16, lane, 1);
#pragma unroll
        for (int q = 0; q < 2; q++) {
#pragma unroll
          for (int r = 0; r < 2; r++) {
            const int b = 16 * q + 2 * r;
            const float f = r ? inv1 : inv0;
            *reinterpret_cast<uint4*>(optr + r * 4096 + q * 64) =
                quad_transpose(pack_bf16(o[b] * f, o[b + 1] * f), pack_bf16(o[b + 4] * f, o[b + 5] * f),
                               pack_bf16(o[b + 8] * f, o[b + 9] * f), pack_bf16(o[b + 12] * f, o[b + 13] * f), b0, b1);
          }
        }
        optr += 128;
      }
    }
  }
}

typedef CUresult (*EncodeTiledFn)(CUtensorMap*, CUtensorMapDataType, cuuint32_t, void*, const cuuint64_t*,
                                  const cuuint64_t*, const cuuint32_t*, const cuuint32_t*, CUtensorMapInterleave,
                                  CUtensorMapSwizzle, CUtensorMapL2promotion, CUtensorMapFloatOOBfill);

CUtensorMap make_map(EncodeTiledFn enc, const void* ptr, uint32_t boxBlocks) {
  CUtensorMap m;
  cuuint64_t dims[3] = {64, (cuuint64_t)kHeads * kSeq, 4};
  cuuint64_t strides[2] = {512, 128};
  cuuint32_t box[3] = {64, 64, boxBlocks};
  cuuint32_t es[3] = {1, 1, 1};
  enc(&m, CU_TENSOR_MAP_DATA_TYPE_BFLOAT16, 3, const_cast<void*>(ptr), dims, strides, box, es,
      CU_TENSOR_MAP_INTERLEAVE_NONE, CU_TENSOR_MAP_SWIZZLE_128B, CU_TENSOR_MAP_L2_PROMOTION_L2_128B,
      CU_TENSOR_MAP_FLOAT_OOB_FILL_NONE);
  return m;
}

}

extern "C" void kernel_launch(void* const* d_in, const int* in_sizes, int n_in, void* d_out, int out_size) {
  static EncodeTiledFn enc = nullptr;
  static int coresident = 0;
  static unsigned int* ticks = nullptr;
  if (!enc) {
    cudaGetSymbolAddress((void**)&ticks, g_ticks);
    void* fn = nullptr;
    cudaDriverEntryPointQueryResult qr;
    cudaGetDriverEntryPoint("cuTensorMapEncodeTiled", &fn, cudaEnableDefault, &qr);
    enc = (EncodeTiledFn)fn;
    cudaFuncSetAttribute(mha_kernel, cudaFuncAttributeMaxDynamicSharedMemorySize, kSmemBytes);
    cudaLaunchConfig_t cfg = {};
    cfg.gridDim = dim3(2 * kClusters), cfg.blockDim = dim3(kThreads), cfg.dynamicSmemBytes = kSmemBytes;
    cudaLaunchAttribute attr;
    attr.id = cudaLaunchAttributeClusterDimension;
    attr.val.clusterDim.x = 2, attr.val.clusterDim.y = 1, attr.val.clusterDim.z = 1;
    cfg.attrs = &attr, cfg.numAttrs = 1;
    int clusters = 0;
    if (cudaOccupancyMaxActiveClusters(&clusters, mha_kernel, &cfg) != cudaSuccess) clusters = 0, (void)cudaGetLastError();
    coresident = clusters >= kClusters;
  }
  const CUtensorMap mq = make_map(enc, d_in[0], 2);
  const CUtensorMap mk = make_map(enc, d_in[1], 1);
  const CUtensorMap mv = make_map(enc, d_in[2], 1);
  mha_kernel<<<2 * kClusters, kThreads, kSmemBytes, cudaStreamPerThread>>>((char*)d_out, ticks, coresident, mq, mk, mv);
}
```

```cpp
#include <cuda_runtime.h>
#include <cuda_bf16.h>
#include <cuda.h>
#include <stdint.h>
#include <type_traits>

namespace {

constexpr int kSeq = 384;
constexpr int kHeads = 512;
constexpr int kHeadBytes = kSeq * 512;
constexpr int kClusters = 64;
constexpr int kRounds = kHeads / kClusters;
constexpr int kSlots = 14;
constexpr int kSlotBytes = 16384;
constexpr int kUnits = 30;
constexpr int kLoads = kRounds * kUnits;
constexpr int kThreads = 512;
constexpr int kSmemBytes = kSlots * kSlotBytes + 1024   + 1024  ;
constexpr uint32_t kEmptyCount = 24;

constexpr int kIssuers = 3;
constexpr int kFirstClusters = 10;
constexpr int kStaggerClocks = 226;
constexpr int kStreamFrom = 190;
constexpr int kPrefBegin = 14, kPrefEnd = 22;
constexpr int kPrefAhead = 4;
constexpr int kPrefUntil = 150;
constexpr int kTicks = (kLoads - kSlots + kIssuers - 1) / kIssuers;
constexpr int kLeadEnd = 105;
constexpr int kLeadExtra = 130;
constexpr int kFadeBegin = 35, kFadeEnd = 65;

constexpr int kIdx(int u) { return u < 4 ? 2 + u : 6 + u; }
constexpr int qIdx(int w, int h) { return w == 0 ? h : 4 + 2 * w + h; }
struct Sched {
  uint32_t cons[kRounds][12];
  uint32_t prod[kLoads];
};
constexpr Sched makeSched() {
  Sched s{};
  int rel[kUnits] = {};
  int n = 0;
  for (int g = 0; g < 3; g++)
    for (int w = 0; w < 3; w++)
      for (int a = 0; a < 4; a++) {
        if (w == 2) rel[n++] = kIdx(g * 4 + a);
        if (g == 2 && (a & 1)) rel[n++] = qIdx(w, a / 2);
      }
  for (int x = 0; x < 12; x++) rel[n++] = 18 + x;
  const int last_v[12] = {4, 5, 6, 8, 9, 10, 12, 13, 15, 18, 19, 20};
  int slot[kLoads] = {};
  uint32_t ent[kRounds][kUnits] = {};
  int uses[kSlots] = {};
  for (int i = 0; i < kLoads; i++) {
    const int h = i / kUnits, u = i % kUnits;
    int sl = i;
    if (i >= kSlots) {
      const int k = (h == kRounds - 1 && u >= 18) ? h * kUnits + last_v[u - 18] : i - kSlots;
      const int prev = (k / kUnits) * kUnits + rel[k % kUnits];
      sl = slot[prev];
      ent[prev / kUnits][prev % kUnits] |= 32u;
    }
    slot[i] = sl;
    ent[h][u] = (uint32_t)(sl | ((uses[sl]++ & 1) << 4));
    int kind = 0, cb = 0, r64 = 0;
    if (u < 2 || (u >= 6 && u < 10)) {
      cb = (u & 1) * 2, r64 = u < 2 ? 0 : (u - 4) / 2;
    } else if (u < 18) {
      const int ku = u < 6 ? u - 2 : u - 6;
      kind = 1, cb = ku & 3, r64 = (ku / 4) * 2;
    } else {
      kind = 2, cb = (u - 18) / 3, r64 = ((u - 18) % 3) * 2;
    }
    const int pref = u >= kPrefBegin && u < kPrefEnd && i < kPrefUntil;
    s.prod[i] = ent[h][u] | (uint32_t)(kind << 5) | (uint32_t)(pref << 7) | (uint32_t)(cb << 8) |
                (uint32_t)((h * kClusters * 6 + r64) << 12);
  }
  for (int h = 0; h < kRounds; h++) {
    for (int g = 0; g < 3; g++)
      for (int a = 0; a < 4; a++) s.cons[h][g] |= ent[h][kIdx(g * 4 + a)] << (8 * a);
    for (int c = 0; c < 4; c++)
      for (int a = 0; a < 3; a++) s.cons[h][3 + c] |= ent[h][18 + c * 3 + a] << (8 * a);
    for (int w = 0; w < 3; w++)
      for (int a = 0; a < 2; a++) s.cons[h][8 + w] |= ent[h][qIdx(w, a)] << (8 * a);
  }
  return s;
}
static_assert(kPrefBegin + kPrefAhead >= 18 && kPrefEnd - 1 + kPrefAhead < kUnits, "prefetch targets must be V tiles");
__constant__ Sched c_sched = makeSched();

__host__ __device__ constexpr uint32_t first_entry(int i) {
  const bool q = (0x3C3 >> i) & 1;
  const int ku = i < 6 ? i - 2 : i - 6;
  return (uint32_t)(i | (q ? ((i & 1) << 9) | ((i < 2 ? 0 : (i - 4) >> 1) << 12) : 32 | ((ku & 3) << 8) | ((ku >> 2) << 13)));
}
constexpr bool first_entries_ok() {
  const Sched s = makeSched();
  for (int i = 0; i < kSlots; i++)
    if (s.prod[i] != first_entry(i)) return false;
  return true;
}
static_assert(first_entries_ok(), "first_entry() must match the schedule table");

__device__ unsigned int g_ticks;

__device__ __forceinline__ uint32_t smem_u32(const void* p) { return (uint32_t)__cvta_generic_to_shared(p); }
__device__ __forceinline__ void mbar_init(uint32_t bar, uint32_t cnt) {
  asm volatile("mbarrier.init.shared::cta.b64 [%0], %1;" ::"r"(bar), "r"(cnt) : "memory");
}
__device__ __forceinline__ void mbar_wait(uint32_t bar, uint32_t parity) {
  asm volatile(
      "{\n"
      ".reg .pred p;\n"
      ".reg .u32 n;\n"
      "mov.u32 n, 0;\n"
      "LAB_WAIT:\n"
      "mbarrier.try_wait.parity.shared::cta.b64 p, [%0], %1;\n"
      "@p bra LAB_DONE;\n"
      "add.u32 n, n, 1;\n"
      "setp.lt.u32 p, n, 0x80000;\n"
      "@p bra LAB_WAIT;\n"
      "trap;\n"
      "LAB_DONE:\n"
      "}\n" ::"r"(bar),
      "r"(parity)
      : "memory");
}
__device__ __forceinline__ bool mbar_test(uint32_t bar, uint32_t parity) {
  uint32_t ok;
  asm volatile("{\n.reg .pred p;\nmbarrier.test_wait.parity.shared::cta.b64 p, [%1], %2;\nselp.u32 %0, 1, 0, p;\n}\n"
               : "=r"(ok)
               : "r"(bar), "r"(parity)
               : "memory");
  return ok;
}
__device__ __forceinline__ void wait_full(uint32_t bars, uint32_t entry) { mbar_wait(bars + 8 * (entry & 15u), (entry >> 4) & 1u); }
__device__ __forceinline__ bool test_full(uint32_t bars, uint32_t entry) { return mbar_test(bars + 8 * (entry & 15u), (entry >> 4) & 1u); }
__device__ __forceinline__ uint32_t map_to_cta(uint32_t addr, uint32_t cta) {
  uint32_t r;
  asm("mapa.shared::cluster.u32 %0, %1, %2;" : "=r"(r) : "r"(addr), "r"(cta));
  return r;
}
__device__ __forceinline__ void release_slot(uint32_t bars, uint32_t entry, uint32_t lane, uint32_t count) {
  asm volatile(
      "{\n"
      ".reg .pred p;\n"
      "setp.lt.u32 p, %1, %3;\n"
      "@p mbarrier.arrive.shared::cluster.b64 _, [%0], %2;\n"
      "}\n" ::"r"(bars + 8 * (entry & 15u)),
      "r"(lane), "r"(count), "r"((entry >> 4) & 2u)
      : "memory");
}
__device__ __forceinline__ void tma_load(uint32_t dst, const CUtensorMap* m, uint32_t bar, int row, int cb, uint64_t pol) {
  asm volatile(
      "{\n.reg .pred p;\nelect.sync _|p, 0xffffffff;\n"
      "@p mbarrier.arrive.expect_tx.shared::cta.b64 _, [%2], 16384;\n"
      "@p cp.async.bulk.tensor.3d.shared::cluster.global.mbarrier::complete_tx::bytes.L2::cache_hint"
      " [%0], [%1, {%3, %4, %5}], [%2], %6;\n}\n" ::"r"(dst),
      "l"(m), "r"(bar), "r"(0), "r"(row), "r"(cb), "l"(pol)
      : "memory");
}
__device__ __forceinline__ void tma_load_mc(uint32_t dst, const CUtensorMap* m, uint32_t bar, int row, int cb, uint64_t pol) {
  asm volatile(
      "{\n.reg .pred p;\nelect.sync _|p, 0xffffffff;\n"
      "@p mbarrier.arrive.expect_tx.shared::cta.b64 _, [%2], 16384;\n"
      "@p cp.async.bulk.tensor.3d.shared::cluster.global.mbarrier::complete_tx::bytes.multicast::cluster.L2::cache_hint"
      " [%0], [%1, {%3, %4, %5}], [%2], %6, %7;\n}\n" ::"r"(dst),
      "l"(m), "r"(bar), "r"(0), "r"(row), "r"(cb), "h"((uint16_t)3), "l"(pol)
      : "memory");
}
__device__ __forceinline__ void tma_prefetch(const CUtensorMap* m, int row, int cb, uint64_t pol) {
  asm volatile(
      "{\n.reg .pred p;\nelect.sync _|p, 0xffffffff;\n"
      "@p cp.async.bulk.prefetch.tensor.3d.L2.global.L2::cache_hint [%0, {%1, %2, %3}], %4;\n}\n" ::"l"(m),
      "r"(0), "r"(row), "r"(cb), "l"(pol)
      : "memory");
}
__device__ __forceinline__ void cluster_arrive() { asm volatile("barrier.cluster.arrive.relaxed.aligned;" ::: "memory"); }
__device__ __forceinline__ void cluster_wait() { asm volatile("barrier.cluster.wait.aligned;" ::: "memory"); }
__device__ __forceinline__ void turn_wait(int id) { asm volatile("bar.sync %0, 256;" ::"r"(id) : "memory"); }
__device__ __forceinline__ void turn_pass(int id) { asm volatile("bar.arrive %0, 256;" ::"r"(id) : "memory"); }
template <int N>
__device__ __forceinline__ void wg_wait() {
  asm volatile("wgmma.wait_group.sync.aligned %0;" ::"n"(N) : "memory");
}
__device__ __forceinline__ float ex2(float x) {
  float y;
  asm("ex2.approx.ftz.f32 %0, %1;" : "=f"(y) : "f"(x));
  return y;
}
__device__ __forceinline__ float rcp(float x) {
  float y;
  asm("rcp.approx.ftz.f32 %0, %1;" : "=f"(y) : "f"(x));
  return y;
}
__device__ __forceinline__ uint32_t pack_bf16(float lo, float hi) {
  uint32_t r;
  asm("cvt.rn.bf16x2.f32 %0, %1, %2;" : "=r"(r) : "f"(hi), "f"(lo));
  return r;
}
__device__ __forceinline__ void scale_bf16x2(uint32_t& x, uint32_t fh, uint32_t fl) {
  asm("{\n.reg .b32 t;\nmul.rn.bf16x2 t, %0, %2;\nfma.rn.bf16x2 %0, %0, %1, t;\n}\n" : "+r"(x) : "r"(fh), "r"(fl));
}

constexpr uint32_t kDescHi = 64u | (1u << 30);
__device__ __forceinline__ uint32_t desc_lo(uint32_t addr) { return ((addr & 0x3FFFF) >> 4) | (1u << 16); }

#define ACC8(a, o) \
  "+f"(a[o]), "+f"(a[o + 1]), "+f"(a[o + 2]), "+f"(a[o + 3]), "+f"(a[o + 4]), "+f"(a[o + 5]), "+f"(a[o + 6]), "+f"(a[o + 7])
#define IN8(a, o) \
  "r"(a[o]), "r"(a[o + 1]), "r"(a[o + 2]), "r"(a[o + 3]), "r"(a[o + 4]), "r"(a[o + 5]), "r"(a[o + 6]), "r"(a[o + 7])
#define REGS32 "{%0,%1,%2,%3,%4,%5,%6,%7,%8,%9,%10,%11,%12,%13,%14,%15,%16,%17,%18,%19,%20,%21,%22,%23,%24,%25,%26,%27,%28,%29,%30,%31}"
#define REGS64 "{%0,%1,%2,%3,%4,%5,%6,%7,%8,%9,%10,%11,%12,%13,%14,%15,%16,%17,%18,%19,%20,%21,%22,%23,%24,%25,%26,%27,%28,%29,%30,%31,%32,%33,%34,%35,%36,%37,%38,%39,%40,%41,%42,%43,%44,%45,%46,%47,%48,%49,%50,%51,%52,%53,%54,%55,%56,%57,%58,%59,%60,%61,%62,%63}"

__device__ __forceinline__ void mma_qk(float (&d)[64], uint32_t qa, uint32_t kb, int accumulate) {
  asm volatile(
      "{\n.reg .pred p;\n.reg .b32 a, b;\n.reg .b64 da, db;\n"
      "setp.ne.b32 p, %66, 0;\n"
      "wgmma.fence.sync.aligned;\n"
      "mov.b64 da, {%64, %67};\nmov.b64 db, {%65, %67};\n"
      "wgmma.mma_async.sync.aligned.m64n128k16.f32.bf16.bf16 " REGS64 ", da, db, p, 1, 1, 0, 0;\n"
      "add.u32 a, %64, 2;\nadd.u32 b, %65, 2;\nmov.b64 da, {a, %67};\nmov.b64 db, {b, %67};\n"
      "wgmma.mma_async.sync.aligned.m64n128k16.f32.bf16.bf16 " REGS64 ", da, db, 1, 1, 1, 0, 0;\n"
      "add.u32 a, %64, 4;\nadd.u32 b, %65, 4;\nmov.b64 da, {a, %67};\nmov.b64 db, {b, %67};\n"
      "wgmma.mma_async.sync.aligned.m64n128k16.f32.bf16.bf16 " REGS64 ", da, db, 1, 1, 1, 0, 0;\n"
      "add.u32 a, %64, 6;\nadd.u32 b, %65, 6;\nmov.b64 da, {a, %67};\nmov.b64 db, {b, %67};\n"
      "wgmma.mma_async.sync.aligned.m64n128k16.f32.bf16.bf16 " REGS64 ", da, db, 1, 1, 1, 0, 0;\n"
      "wgmma.commit_group.sync.aligned;\n}\n"
      : ACC8(d, 0), ACC8(d, 8), ACC8(d, 16), ACC8(d, 24), ACC8(d, 32), ACC8(d, 40), ACC8(d, 48), ACC8(d, 56)
      : "r"(qa), "r"(kb), "r"(accumulate), "n"(kDescHi)
      : "memory");
}
__device__ __forceinline__ void mma_pv(float (&d)[32], const uint32_t* a, uint32_t vb, int accumulate) {
  asm volatile(
      "{\n.reg .pred p;\n.reg .b32 b;\n.reg .b64 db;\n"
      "setp.ne.b32 p, %65, 0;\n"
      "wgmma.fence.sync.aligned;\n"
      "mov.b64 db, {%64, %66};\n"
      "wgmma.mma_async.sync.aligned.m64n64k16.f32.bf16.bf16 " REGS32 ", {%32,%33,%34,%35}, db, p, 1, 1, 1;\n"
      "add.u32 b, %64, 128;\nmov.b64 db, {b, %66};\n"
      "wgmma.mma_async.sync.aligned.m64n64k16.f32.bf16.bf16 " REGS32 ", {%36,%37,%38,%39}, db, 1, 1, 1, 1;\n"
      "add.u32 b, %64, 256;\nmov.b64 db, {b, %66};\n"
      "wgmma.mma_async.sync.aligned.m64n64k16.f32.bf16.bf16 " REGS32 ", {%40,%41,%42,%43}, db, 1, 1, 1, 1;\n"
      "add.u32 b, %64, 384;\nmov.b64 db, {b, %66};\n"
      "wgmma.mma_async.sync.aligned.m64n64k16.f32.bf16.bf16 " REGS32 ", {%44,%45,%46,%47}, db, 1, 1, 1, 1;\n"
      "add.u32 b, %64, 512;\nmov.b64 db, {b, %66};\n"
      "wgmma.mma_async.sync.aligned.m64n64k16.f32.bf16.bf16 " REGS32 ", {%48,%49,%50,%51}, db, 1, 1, 1, 1;\n"
      "add.u32 b, %64, 640;\nmov.b64 db, {b, %66};\n"
      "wgmma.mma_async.sync.aligned.m64n64k16.f32.bf16.bf16 " REGS32 ", {%52,%53,%54,%55}, db, 1, 1, 1, 1;\n"
      "add.u32 b, %64, 768;\nmov.b64 db, {b, %66};\n"
      "wgmma.mma_async.sync.aligned.m64n64k16.f32.bf16.bf16 " REGS32 ", {%56,%57,%58,%59}, db, 1, 1, 1, 1;\n"
      "add.u32 b, %64, 896;\nmov.b64 db, {b, %66};\n"
      "wgmma.mma_async.sync.aligned.m64n64k16.f32.bf16.bf16 " REGS32 ", {%60,%61,%62,%63}, db, 1, 1, 1, 1;\n"
      "wgmma.commit_group.sync.aligned;\n}\n"
      : ACC8(d, 0), ACC8(d, 8), ACC8(d, 16), ACC8(d, 24)
      : IN8(a, 0), IN8(a, 8), IN8(a, 16), IN8(a, 24), "r"(vb), "r"(accumulate), "n"(kDescHi)
      : "memory");
}
template <int N>
__device__ __forceinline__ void keep_regs(float (&d)[N]) {
#pragma unroll
  for (int i = 0; i < N; i++) asm volatile("" : "+f"(d[i])::"memory");
}

__device__ __forceinline__ uint4 quad_transpose(uint32_t a0, uint32_t a1, uint32_t a2, uint32_t a3, bool b0, bool b1) {
  uint32_t s0 = b0 ? a0 : a1, s1 = b0 ? a2 : a3;
  uint32_t r0 = __shfl_xor_sync(0xffffffffu, s0, 1), r1 = __shfl_xor_sync(0xffffffffu, s1, 1);
  uint32_t c0 = b0 ? r0 : a0, c1 = b0 ? a1 : r0, c2 = b0 ? r1 : a2, c3 = b0 ? a3 : r1;
  uint32_t t0 = b1 ? c0 : c2, t1 = b1 ? c1 : c3;
  uint32_t u0 = __shfl_xor_sync(0xffffffffu, t0, 2), u1 = __shfl_xor_sync(0xffffffffu, t1, 2);
  uint4 r;
  r.x = b1 ? u0 : c0;
  r.y = b1 ? u1 : c1;
  r.z = b1 ? c2 : u0;
  r.w = b1 ? c3 : u1;
  return r;
}

constexpr float kScaleLog2 = 0.0625f * 1.4426950408889634f;
constexpr float kRescaleThreshold = 8.f;

template <int N>
__device__ __forceinline__ void rescale_p(uint32_t* P, float f0, float f1) {
  const uint32_t h0 = pack_bf16(f0, f0), h1 = pack_bf16(f1, f1);
  const float r0 = f0 - __uint_as_float(h0 << 16), r1 = f1 - __uint_as_float(h1 << 16);
  const uint32_t l0 = pack_bf16(r0, r0), l1 = pack_bf16(r1, r1);
#pragma unroll
  for (int i = 0; i < N / 2; i++) {
    scale_bf16x2(P[2 * i], h0, l0);
    scale_bf16x2(P[2 * i + 1], h1, l1);
  }
}
__device__ __forceinline__ void row_max_float(const float (&s)[64], float& mx0, float& mx1) {
  mx0 = fmaxf(s[0], s[1]), mx1 = fmaxf(s[2], s[3]);
#pragma unroll
  for (int i = 1; i < 16; i++) {
    mx0 = fmaxf(mx0, fmaxf(s[4 * i], s[4 * i + 1]));
    mx1 = fmaxf(mx1, fmaxf(s[4 * i + 2], s[4 * i + 3]));
  }
  mx0 = fmaxf(mx0, __shfl_xor_sync(0xffffffffu, mx0, 1));
  mx1 = fmaxf(mx1, __shfl_xor_sync(0xffffffffu, mx1, 1));
  mx0 = fmaxf(mx0, __shfl_xor_sync(0xffffffffu, mx0, 2));
  mx1 = fmaxf(mx1, __shfl_xor_sync(0xffffffffu, mx1, 2));
}
__device__ __forceinline__ void row_max_int(const float (&s)[64], float& mx0, float& mx1) {
  int a0 = max(__float_as_int(s[0]), __float_as_int(s[1])), a1 = max(__float_as_int(s[2]), __float_as_int(s[3]));
  int b0 = max(__float_as_int(s[4]), __float_as_int(s[5])), b1 = max(__float_as_int(s[6]), __float_as_int(s[7]));
#pragma unroll
  for (int i = 1; i < 8; i++) {
    a0 = __vimax3_s32(a0, __float_as_int(s[8 * i]), __float_as_int(s[8 * i + 1]));
    a1 = __vimax3_s32(a1, __float_as_int(s[8 * i + 2]), __float_as_int(s[8 * i + 3]));
    b0 = __vimax3_s32(b0, __float_as_int(s[8 * i + 4]), __float_as_int(s[8 * i + 5]));
    b1 = __vimax3_s32(b1, __float_as_int(s[8 * i + 6]), __float_as_int(s[8 * i + 7]));
  }
  a0 = max(a0, b0);
  a1 = max(a1, b1);
  a0 = max(a0, __shfl_xor_sync(0xffffffffu, a0, 1));
  a1 = max(a1, __shfl_xor_sync(0xffffffffu, a1, 1));
  a0 = max(a0, __shfl_xor_sync(0xffffffffu, a0, 2));
  a1 = max(a1, __shfl_xor_sync(0xffffffffu, a1, 2));
  mx0 = __int_as_float(a0);
  mx1 = __int_as_float(a1);
}

template <int J>
__device__ __forceinline__ void softmax_chunk(float (&s)[64], uint32_t (&P)[96], float (&m)[2], float (&l)[2]) {
  float mx0, mx1;
  row_max_int(s, mx0, mx1);
  bool redo = (__float_as_int(mx0) | __float_as_int(mx1)) < 0;
  if (J > 0)
    redo = redo || fmaf(mx0, kScaleLog2, -m[0]) > kRescaleThreshold || fmaf(mx1, kScaleLog2, -m[1]) > kRescaleThreshold;
  if (__any_sync(0xffffffffu, redo)) {
    row_max_float(s, mx0, mx1);
    if (J > 0) {
      const float n0 = fmaxf(m[0], mx0 * kScaleLog2), n1 = fmaxf(m[1], mx1 * kScaleLog2);
      const float f0 = ex2(m[0] - n0), f1 = ex2(m[1] - n1);
      rescale_p<32 * J>(P, f0, f1);
      l[0] *= f0, l[1] *= f1;
      m[0] = n0, m[1] = n1;
    }
  }
  if (J == 0) m[0] = mx0 * kScaleLog2, m[1] = mx1 * kScaleLog2;
  float a0 = J ? l[0] : 0.f, a1 = J ? l[1] : 0.f, b0 = 0.f, b1 = 0.f;
#pragma unroll
  for (int ii = 0; ii < 16; ii++) {
    const int i = ii ^ 8;
    s[4 * i] = ex2(fmaf(s[4 * i], kScaleLog2, -m[0]));
    s[4 * i + 1] = ex2(fmaf(s[4 * i + 1], kScaleLog2, -m[0]));
    s[4 * i + 2] = ex2(fmaf(s[4 * i + 2], kScaleLog2, -m[1]));
    s[4 * i + 3] = ex2(fmaf(s[4 * i + 3], kScaleLog2, -m[1]));
    a0 += s[4 * i];
    b0 += s[4 * i + 1];
    a1 += s[4 * i + 2];
    b1 += s[4 * i + 3];
    P[32 * J + 2 * i] = pack_bf16(s[4 * i], s[4 * i + 1]);
    P[32 * J + 2 * i + 1] = pack_bf16(s[4 * i + 2], s[4 * i + 3]);
  }
  l[0] = a0 + b0;
  l[1] = a1 + b1;
}

__global__ void __cluster_dims__(2, 1, 1) __launch_bounds__(kThreads, 1)
    mha_kernel(char* __restrict__ out, unsigned int* ticks, const int coresident, const __grid_constant__ CUtensorMap mapQ,
               const __grid_constant__ CUtensorMap mapK, const __grid_constant__ CUtensorMap mapV) {
  extern __shared__ unsigned char smem_raw[];
  const uint32_t base = (smem_u32(smem_raw) + 1023u) & ~1023u;
  const uint32_t bar_full = base + kSlots * kSlotBytes;
  const uint32_t bar_empty = bar_full + 128;
  const int wg = __shfl_sync(0xffffffffu, (int)(threadIdx.x >> 7), 0);
  const int rank = blockIdx.x & 1;
  const int cid = blockIdx.x >> 1;

  if (wg == 3) {
    const uint32_t t_entry = clock();
    const uint32_t pace_word = bar_full + 256;
    const int pw = __shfl_sync(0xffffffffu, (int)(threadIdx.x >> 5) & 3, 0);
    if ((threadIdx.x & 31) == 0) {
      if (pw < 2) {
#pragma unroll
        for (int i = 0; i < kSlots; i++) mbar_init((pw ? bar_empty : bar_full) + 8 * i, pw ? kEmptyCount : 1);
        asm volatile("fence.mbarrier_init.release.cluster;" ::: "memory");
      } else if (pw == 2) {
        asm volatile("prefetch.tensormap [%0];" ::"l"(&mapQ) : "memory");
        asm volatile("prefetch.tensormap [%0];" ::"l"(&mapK) : "memory");
        asm volatile("prefetch.tensormap [%0];" ::"l"(&mapV) : "memory");
      } else {
        asm volatile("st.shared.v2.u32 [%0], {%1, %1};" ::"r"(pace_word), "r"(0) : "memory");
      }
    }
    asm volatile("bar.sync 4, 128;" ::: "memory");
    cluster_arrive();
    uint64_t pol_stream, pol_normal;
    asm volatile("createpolicy.fractional.L2::evict_normal.b64 %0, 1.0;" : "=l"(pol_normal));
    auto issue = [&](uint32_t e, uint64_t pol) {
      const uint32_t sl = e & 15u, kind = (e >> 5) & 3u;
      const uint32_t dst = base + sl * kSlotBytes, fb = bar_full + 8 * sl;
      const int row = (int)(e >> 12) * 64 + cid * kSeq, cb = (e >> 8) & 3u;
      if (kind == 0) tma_load(dst, &mapQ, fb, row + rank * 192, cb, pol);
      else tma_load_mc(dst + rank * 8192, kind == 1 ? &mapK : &mapV, fb, row + rank * 64, cb, pol);
    };
    if (pw >= 2) cluster_wait();
    if (coresident) {
      const uint32_t delay = max(cid - kFirstClusters, 0) * kStaggerClocks;
      while ((uint32_t)clock() - t_entry < delay) __nanosleep(20);
    }
    issue(first_entry(pw), pol_normal);
    asm volatile("setmaxnreg.dec.sync.aligned.u32 32;");
    if (pw < 2) cluster_wait();
#pragma unroll 1
    for (int i = pw + 4; i < kSlots; i += 4) issue(first_entry(i), pol_normal);

    if (pw == kIssuers) {
      if (rank == 0 && coresident) {
#pragma unroll 1
        for (int n = 0; n < (1 << 16); n++) {
          uint32_t seen, done;
          asm volatile("ld.relaxed.gpu.global.u32 %0, [%1];" : "=r"(seen) : "l"(ticks) : "memory");
          asm volatile("st.volatile.shared.u32 [%0], %1;" ::"r"(pace_word), "r"(seen) : "memory");
          asm volatile("ld.volatile.shared.u32 %0, [%1];" : "=r"(done) : "r"(pace_word + 4) : "memory");
          if (done) break;
          __nanosleep(100);
        }
      }
    } else {
      const bool pacer = pw == 0 && rank == 0 && coresident;
      asm volatile("createpolicy.fractional.L2::evict_first.b64 %0, 1.0;" : "=l"(pol_stream));
      int tick = 0, patience = 512;
#pragma unroll 1
      for (int i = kSlots + pw; i < kLoads; i += kIssuers) {
        const uint32_t e = c_sched.prod[i];
        mbar_wait(bar_empty + 8 * (e & 15u), ((e >> 4) & 1u) ^ 1u);
        if (pacer) {
          const int lead = kLeadEnd + kLeadExtra * min(max(kFadeEnd - tick, 0), kFadeEnd - kFadeBegin) / (kFadeEnd - kFadeBegin);
#pragma unroll 1
          for (; patience > 0; patience--) {
            uint32_t seen;
            asm volatile("ld.volatile.shared.u32 %0, [%1];" : "=r"(seen) : "r"(pace_word) : "memory");
            if (tick * kClusters - (int)seen <= lead) break;
            __nanosleep(40);
          }
          tick++;
        }
        issue(e, i >= kStreamFrom ? pol_stream : pol_normal);
        if (e & 128u) {
          const uint32_t en = c_sched.prod[i + kPrefAhead];
          tma_prefetch(&mapV, (int)(en >> 12) * 64 + cid * kSeq + rank * 64, (en >> 8) & 3u, pol_normal);
        }
        if (pacer && (threadIdx.x & 31) == 0)
          asm volatile("red.relaxed.gpu.global.inc.u32 [%0], %1;" ::"l"(ticks), "r"(kTicks * kClusters - 1) : "memory");
      }
      if (pacer) asm volatile("st.volatile.shared.u32 [%0], %1;" ::"r"(pace_word + 4), "r"(1) : "memory");
    }
  } else {
    cluster_arrive();
    asm volatile("setmaxnreg.inc.sync.aligned.u32 160;");
    const uint32_t lane = threadIdx.x & 31;
    const uint32_t dbase = desc_lo(base);
    const uint32_t rel_bar = map_to_cta(bar_empty, lane & 1);
    const int my_turn = 1 + wg, next_turn = 1 + (wg == 2 ? 0 : wg + 1);
    cluster_wait();
    if (wg == 2) turn_pass(1);
    const bool b0 = lane & 1, b1 = lane & 2;
    const uint32_t out_off =
        (uint32_t)(rank * 192 + wg * 64 + ((threadIdx.x >> 5) & 3) * 16 + (lane >> 2)) * 512u + (lane & 3) * 16u;

#pragma unroll 1
    for (int h = 0; h < kRounds; h++) {
      uint32_t P[96];
      float m[2], l[2];
      const uint32_t qw = c_sched.cons[h][8 + wg];

      auto qk_chunk = [&](auto jc) {
        constexpr int j = decltype(jc)::value;
        float s[64];
        const uint32_t kw = c_sched.cons[h][j];
        if (j == 0) wait_full(bar_full, qw);
        wait_full(bar_full, kw);
        turn_wait(my_turn);
#pragma unroll
        for (int cb = 0; cb < 4; cb++) {
          const uint32_t e = kw >> (8 * cb);
          bool ready = true;
          if (cb < 3) ready = test_full(bar_full, e >> 8);
          if (j == 0 && cb == 1) ready = ready && test_full(bar_full, qw >> 8);
          mma_qk(s, dbase + ((cb < 2 ? qw : qw >> 8) & 15u) * 1024 + (cb & 1) * 512, dbase + (e & 15u) * 1024, cb != 0);
          if (cb > 0) {
            wg_wait<1>();
            if (cb == 3) turn_pass(next_turn);
            release_slot(rel_bar, kw >> (8 * cb - 8), lane, 1);
            if (j == 2 && cb == 2) release_slot(rel_bar, qw, lane, 3);
          }
          if (!ready) {
            if (j == 0 && cb == 1) wait_full(bar_full, qw >> 8);
            wait_full(bar_full, e >> 8);
          }
        }
        wg_wait<0>();
        keep_regs(s);
        release_slot(rel_bar, kw >> 24, lane, 1);
        if (j == 2) release_slot(rel_bar, qw >> 8, lane, 3);
        softmax_chunk<j>(s, P, m, l);
      };
      qk_chunk(std::integral_constant<int, 0>{});
      qk_chunk(std::integral_constant<int, 1>{});
      qk_chunk(std::integral_constant<int, 2>{});
      l[0] += __shfl_xor_sync(0xffffffffu, l[0], 1);
      l[1] += __shfl_xor_sync(0xffffffffu, l[1], 1);
      l[0] += __shfl_xor_sync(0xffffffffu, l[0], 2);
      l[1] += __shfl_xor_sync(0xffffffffu, l[1], 2);
      const float inv0 = rcp(l[0]), inv1 = rcp(l[1]);

      char* optr = out + (size_t)(cid + h * kClusters) * kHeadBytes + out_off;
#pragma unroll 1
      for (int c = 0; c < 4; c++) {
        float o[32];
        const uint32_t vw = c_sched.cons[h][3 + c];
        wait_full(bar_full, vw);
        turn_wait(my_turn);
#pragma unroll
        for (int j = 0; j < 3; j++) {
          const uint32_t e = vw >> (8 * j);
          bool ready = true;
          if (j < 2) ready = test_full(bar_full, e >> 8);
          mma_pv(o, P + 32 * j, dbase + (e & 15u) * 1024, j != 0);
          if (j > 0) {
            wg_wait<1>();
            if (j == 2 && !(wg == 2 && c == 3 && h == kRounds - 1)) turn_pass(next_turn);
            release_slot(rel_bar, vw >> (8 * j - 8), lane, 1);
          }
          if (!ready) wait_full(bar_full, e >> 8);
        }
        wg_wait<0>();
        keep_regs(o);
        release_slot(rel_bar, vw >> 16, lane, 1);
#pragma unroll
        for (int q = 0; q < 2; q++) {
#pragma unroll
          for (int r = 0; r < 2; r++) {
            const int b = 16 * q + 2 * r;
            const float f = r ? inv1 : inv0;
            *reinterpret_cast<uint4*>(optr + r * 4096 + q * 64) =
                quad_transpose(pack_bf16(o[b] * f, o[b + 1] * f), pack_bf16(o[b + 4] * f, o[b + 5] * f),
                               pack_bf16(o[b + 8] * f, o[b + 9] * f), pack_bf16(o[b + 12] * f, o[b + 13] * f), b0, b1);
          }
        }
        optr += 128;
      }
    }
  }
}

typedef CUresult (*EncodeTiledFn)(CUtensorMap*, CUtensorMapDataType, cuuint32_t, void*, const cuuint64_t*,
                                  const cuuint64_t*, const cuuint32_t*, const cuuint32_t*, CUtensorMapInterleave,
                                  CUtensorMapSwizzle, CUtensorMapL2promotion, CUtensorMapFloatOOBfill);

CUtensorMap make_map(EncodeTiledFn enc, const void* ptr, uint32_t boxBlocks) {
  CUtensorMap m;
  cuuint64_t dims[3] = {64, (cuuint64_t)kHeads * kSeq, 4};
  cuuint64_t strides[2] = {512, 128};
  cuuint32_t box[3] = {64, 64, boxBlocks};
  cuuint32_t es[3] = {1, 1, 1};
  enc(&m, CU_TENSOR_MAP_DATA_TYPE_BFLOAT16, 3, const_cast<void*>(ptr), dims, strides, box, es,
      CU_TENSOR_MAP_INTERLEAVE_NONE, CU_TENSOR_MAP_SWIZZLE_128B, CU_TENSOR_MAP_L2_PROMOTION_L2_128B,
      CU_TENSOR_MAP_FLOAT_OOB_FILL_NONE);
  return m;
}

}

extern "C" void kernel_launch(void* const* d_in, const int* in_sizes, int n_in, void* d_out, int out_size) {
  static EncodeTiledFn enc = nullptr;
  static int coresident = 0;
  static unsigned int* ticks = nullptr;
  if (!enc) {
    cudaGetSymbolAddress((void**)&ticks, g_ticks);
    void* fn = nullptr;
    cudaDriverEntryPointQueryResult qr;
    cudaGetDriverEntryPoint("cuTensorMapEncodeTiled", &fn, cudaEnableDefault, &qr);
    enc = (EncodeTiledFn)fn;
    cudaFuncSetAttribute(mha_kernel, cudaFuncAttributeMaxDynamicSharedMemorySize, kSmemBytes);
    cudaLaunchConfig_t cfg = {};
    cfg.gridDim = dim3(2 * kClusters), cfg.blockDim = dim3(kThreads), cfg.dynamicSmemBytes = kSmemBytes;
    cudaLaunchAttribute attr;
    attr.id = cudaLaunchAttributeClusterDimension;
    attr.val.clusterDim.x = 2, attr.val.clusterDim.y = 1, attr.val.clusterDim.z = 1;
    cfg.attrs = &attr, cfg.numAttrs = 1;
    int clusters = 0;
    if (cudaOccupancyMaxActiveClusters(&clusters, mha_kernel, &cfg) != cudaSuccess) clusters = 0, (void)cudaGetLastError();
    coresident = clusters >= kClusters;
  }
  const CUtensorMap mq = make_map(enc, d_in[0], 2);
  const CUtensorMap mk = make_map(enc, d_in[1], 1);
  const CUtensorMap mv = make_map(enc, d_in[2], 1);
  mha_kernel<<<2 * kClusters, kThreads, kSmemBytes, cudaStreamPerThread>>>((char*)d_out, ticks, coresident, mq, mk, mv);
}
```
